```python
import torch

def _softmax(x, axis=-1):
    return torch.softmax(x, dim=axis)
def _gelu(x):
    return torch.nn.functional.gelu(x, approximate="tanh")
def _silu(x):
    return torch.nn.functional.silu(x)
def _sigmoid(x):
    return torch.sigmoid(x)
def _layernorm(x, axis=-1, eps=1e-5):
    m = x.mean(dim=axis, keepdim=True)
    v = x.var(dim=axis, keepdim=True, unbiased=False)
    return (x - m) / torch.sqrt(v + eps)
def _scatter_add(tgt, idx, src, axis=0):
    return tgt.clone().index_add_(axis, idx, src)
def _segment_sum(src, seg, n):
    out = torch.zeros((n,) + src.shape[1:], dtype=src.dtype)
    return out.index_add_(0, seg, src)
def _pad(x, pw):
    flat = tuple(v for pair in reversed(pw) for v in pair)
    return torch.nn.functional.pad(x, flat)

kernel_name = 'standalone__gqa_block_cached__decode'

def setup_inputs():

    _w = (lambda a: (lambda t: t.to(torch.bfloat16) if t.is_floating_point() else t)(torch.as_tensor(a)))
    B, Sq, D = 2, 1, 576
    Hq, Hkv, Sk, Dh = 32, 16, 32768, 128
    assert Hq % Hkv == 0, (Hq, Hkv)
    return {
        "x": _w((lambda *s: torch.randn(*s, dtype=torch.bfloat16) * 0.8)(B, Sq, D)),
        "k_cache": _w((lambda *s: torch.randn(*s, dtype=torch.bfloat16) * 0.8)(B, Hkv, Sk, Dh)),
        "v_cache": _w((lambda *s: torch.randn(*s, dtype=torch.bfloat16) * 0.05)(B, Hkv, Sk, Dh)),
        "wq": _w((lambda *s: torch.randn(*s, dtype=torch.bfloat16) * 0.8)(D, Hq * Dh) * (D ** -0.5)),
        "wo": _w((lambda *s: torch.randn(*s, dtype=torch.bfloat16) * 0.05)(Hq * Dh, D) * ((Hq * Dh) ** -0.5)),
    }

def reference(x, k_cache, v_cache, wq, wo):
    B, Sq, D = x.shape
    Hq, Dh = 32, 128
    Hkv = k_cache.shape[1]
    rep = Hq // Hkv
    q = (lambda x, *d: x.permute(*d))((x @ wq).reshape(B, Sq, Hq, Dh), 0, 2, 1, 3)
    k = (lambda x, n, axis: torch.repeat_interleave(x, n, dim=axis))(k_cache, rep, axis=1)
    v = (lambda x, n, axis: torch.repeat_interleave(x, n, dim=axis))(v_cache, rep, axis=1)
    scores = torch.einsum("bhqd,bhkd->bhqk", q, k) * (Dh ** -0.5)
    p = _softmax(scores, axis=-1)
    o = torch.einsum("bhqk,bhkd->bhqd", p, v)
    return (lambda x, *d: x.permute(*d))(o, 0, 2, 1, 3).reshape(B, Sq, Hq * Dh) @ wo
```

```cpp
#include <cuda_runtime.h>
#include <cuda.h>
#include <cuda_bf16.h>
#include <stdint.h>

namespace {

constexpr int BATCH = 2, DM = 576, HQ = 32, HKV = 16, SK = 32768, DH = 128;
constexpr int NG = BATCH * HKV;
constexpr int QN = HQ * DH;
constexpr int TILE = 64;
constexpr int NCW = TILE / 16;
constexpr int STAGES = 4;
constexpr int TILE_BYTES = TILE * DH * 2;
constexpr int STAGE_BYTES = 2 * TILE_BYTES;
constexpr int TILES_PER_G = SK / TILE;
constexpr int NTILES = NG * TILES_PER_G;
constexpr int NWORK = 8;
constexpr int NTHREADS = (NWORK + 1) * 32;
constexpr int NSLICE = 128;
constexpr int MAX_CTAS = 144;
constexpr int REC_W = 36;
constexpr int WO_SLICE_BYTES = 32 * DM * 2;

constexpr int SM_RING = 0;
constexpr int SM_WO = SM_RING + STAGES * STAGE_BYTES;
constexpr int SM_Q = SM_WO + WO_SLICE_BYTES;
constexpr int SM_PART = SM_Q + BATCH * QN * 2;
constexpr int SM_ML = SM_PART + 2 * NCW * 2 * DH * 4;
constexpr int SM_X = SM_ML + 2 * NCW * 4 * 4;
constexpr int SM_RED = SM_X + BATCH * DM * 4;
constexpr int SM_W = SM_RED + 8 * 64 * 4;
constexpr int SM_O = SM_W + 2 * MAX_CTAS * 4;
constexpr int SM_BAR = SM_O + 64 * 4;
constexpr int SM_TID = SM_BAR + (2 * STAGES + 1) * 8;
constexpr int SM_TOTAL = SM_TID + STAGES * 4 + 64;
constexpr int SMEM_BYTES = SM_TOTAL + 1024;

static_assert(2 * MAX_CTAS * REC_W * 4 <= STAGES * STAGE_BYTES, "ring too small for record staging");
static_assert(SMEM_BYTES <= 232448, "too much shared memory");

__device__ unsigned int g_tile_counter;
__device__ unsigned int g_q_ready;
__device__ __align__(16) __nv_bfloat16 g_q[BATCH * QN];
__device__ __align__(16) float g_rec[NG * 2 * 4 * MAX_CTAS * REC_W];
__device__ __align__(16) float g_pout[NSLICE * NSLICE * 9];

__device__ __forceinline__ uint32_t smem_u32(const void* p) { return (uint32_t)__cvta_generic_to_shared(p); }
__device__ __forceinline__ void mbar_init(uint32_t bar, uint32_t cnt) {
    asm volatile("mbarrier.init.shared::cta.b64 [%0], %1;" ::"r"(bar), "r"(cnt));
}
__device__ __forceinline__ void mbar_expect_tx(uint32_t bar, uint32_t bytes) {
    asm volatile("mbarrier.arrive.expect_tx.shared::cta.b64 _, [%0], %1;" ::"r"(bar), "r"(bytes) : "memory");
}
__device__ __forceinline__ void mbar_arrive(uint32_t bar) {
    asm volatile("mbarrier.arrive.shared::cta.b64 _, [%0];" ::"r"(bar) : "memory");
}
__device__ __forceinline__ void mbar_wait(uint32_t bar, uint32_t parity) {
    uint32_t done;
    for (uint32_t it = 0;; it++) {
        asm volatile(
            "{\n.reg .pred p;\n"
            "mbarrier.try_wait.parity.shared::cta.b64 p, [%1], %2;\n"
            "selp.u32 %0, 1, 0, p;\n}\n"
            : "=r"(done)
            : "r"(bar), "r"(parity)
            : "memory");
        if (done) break;
        if (it > (1u << 24)) __trap();
    }
}
__device__ __forceinline__ void tma_load_3d(uint32_t dst, const CUtensorMap* m, int row, uint32_t bar, uint64_t pol) {
    asm volatile(
        "cp.async.bulk.tensor.3d.shared::cluster.global.mbarrier::complete_tx::bytes.L2::cache_hint "
        "[%0], [%1, {%3, %4, %5}], [%2], %6;" ::"r"(dst),
        "l"((uint64_t)m), "r"(bar), "r"(0), "r"(row), "r"(0), "l"(pol)
        : "memory");
}
__device__ __forceinline__ void bulk_load(uint32_t dst, const void* src, uint32_t bytes, uint32_t bar) {
    asm volatile("cp.async.bulk.shared::cluster.global.mbarrier::complete_tx::bytes [%0], [%1], %2, [%3];" ::"r"(dst),
                 "l"(src), "r"(bytes), "r"(bar)
                 : "memory");
}
__device__ __forceinline__ void ldsm_x4(uint32_t (&r)[4], uint32_t addr) {
    asm volatile("ldmatrix.sync.aligned.m8n8.x4.shared.b16 {%0,%1,%2,%3}, [%4];"
                 : "=r"(r[0]), "=r"(r[1]), "=r"(r[2]), "=r"(r[3])
                 : "r"(addr)
                 : "memory");
}
__device__ __forceinline__ void ldsm_x4_t(uint32_t (&r)[4], uint32_t addr) {
    asm volatile("ldmatrix.sync.aligned.m8n8.x4.trans.shared.b16 {%0,%1,%2,%3}, [%4];"
                 : "=r"(r[0]), "=r"(r[1]), "=r"(r[2]), "=r"(r[3])
                 : "r"(addr)
                 : "memory");
}
__device__ __forceinline__ void mma_bf16(float (&c)[4], uint32_t a0, uint32_t a1, uint32_t a2, uint32_t a3, uint32_t b0,
                                         uint32_t b1) {
    asm volatile(
        "mma.sync.aligned.m16n8k16.row.col.f32.bf16.bf16.f32 {%0,%1,%2,%3}, {%4,%5,%6,%7}, {%8,%9}, {%0,%1,%2,%3};"
        : "+f"(c[0]), "+f"(c[1]), "+f"(c[2]), "+f"(c[3])
        : "r"(a0), "r"(a1), "r"(a2), "r"(a3), "r"(b0), "r"(b1));
}
__device__ __forceinline__ float ex2(float x) {
    float y;
    asm("ex2.approx.ftz.f32 %0, %1;" : "=f"(y) : "f"(x));
    return y;
}
__device__ __forceinline__ uint32_t pack_bf16(float lo, float hi) {
    uint32_t r;
    asm("cvt.rn.bf16x2.f32 %0, %1, %2;" : "=r"(r) : "f"(hi), "f"(lo));
    return r;
}
__device__ __forceinline__ void named_bar(int id, int n) { asm volatile("bar.sync %0, %1;" ::"r"(id), "r"(n) : "memory"); }
__device__ __forceinline__ float nz(float v) { return (__float_as_uint(v) == 0u) ? __uint_as_float(0x80000000u) : v; }
__device__ __forceinline__ uint4 ld_relaxed_v4(const void* p) {
    uint4 v;
    asm volatile("ld.relaxed.gpu.global.v4.u32 {%0,%1,%2,%3}, [%4];"
                 : "=r"(v.x), "=r"(v.y), "=r"(v.z), "=r"(v.w)
                 : "l"(p)
                 : "memory");
    return v;
}
__device__ __forceinline__ bool all_nz(const uint4& v) { return v.x != 0u && v.y != 0u && v.z != 0u && v.w != 0u; }
__device__ __forceinline__ float bf_lo(uint32_t u) { return __uint_as_float(u << 16); }
__device__ __forceinline__ float bf_hi(uint32_t u) { return __uint_as_float(u & 0xffff0000u); }

__global__ void __launch_bounds__(NTHREADS, 1)
gqa_decode_kernel(const __grid_constant__ CUtensorMap map_k, const __grid_constant__ CUtensorMap map_v,
                  const __nv_bfloat16* __restrict__ x, const __nv_bfloat16* __restrict__ wq,
                  const __nv_bfloat16* __restrict__ wo, __nv_bfloat16* __restrict__ out) {
    extern __shared__ uint8_t smem_raw[];
    uint8_t* smem = (uint8_t*)(((uintptr_t)smem_raw + 1023) & ~(uintptr_t)1023);
    const uint32_t sbase = smem_u32(smem);
    const int tid = threadIdx.x, warp = tid >> 5, lane = tid & 31;
    const int nc = gridDim.x, cta = blockIdx.x;
    const uint32_t bar_full = sbase + SM_BAR, bar_empty = bar_full + STAGES * 8, bar_wo = bar_full + 2 * STAGES * 8;
    volatile int* tile_id = (volatile int*)(smem + SM_TID);

    if (warp == NWORK) {
        if (lane == 0) {
            for (int s = 0; s < STAGES; s++) {
                mbar_init(bar_full + s * 8, 1);
                mbar_init(bar_empty + s * 8, NCW);
            }
            mbar_init(bar_wo, 1);
            asm volatile("fence.mbarrier_init.release.cluster;" ::: "memory");
            asm volatile("fence.proxy.async.shared::cta;" ::: "memory");
        }
        __syncwarp();
        named_bar(0, NTHREADS);
        if (lane == 0) {
            uint64_t pol;
            asm volatile("createpolicy.fractional.L2::evict_first.b64 %0, 1.0;" : "=l"(pol));
            unsigned nxt = atomicAdd(&g_tile_counter, 1u);
            int s = 0;
            uint32_t ph = 1;
            for (int i = 0; i < STAGES; i++) {
                int t = cta + i * nc;
                tile_id[i] = t;
                mbar_expect_tx(bar_full + i * 8, STAGE_BYTES);
                tma_load_3d(sbase + SM_RING + i * STAGE_BYTES, &map_k, t * TILE, bar_full + i * 8, pol);
                tma_load_3d(sbase + SM_RING + i * STAGE_BYTES + TILE_BYTES, &map_v, t * TILE, bar_full + i * 8, pol);
            }
            ph = 0;
            if (cta < NSLICE) {
                mbar_expect_tx(bar_wo, WO_SLICE_BYTES);
                bulk_load(sbase + SM_WO, (const uint8_t*)wo + (size_t)cta * WO_SLICE_BYTES, WO_SLICE_BYTES, bar_wo);
            }
            const int dyn_base = STAGES * nc;
            while (true) {
                int t = dyn_base + (int)nxt;
                if (t >= NTILES) break;
                nxt = atomicAdd(&g_tile_counter, 1u);
                mbar_wait(bar_empty + s * 8, ph);
                tile_id[s] = t;
                mbar_expect_tx(bar_full + s * 8, STAGE_BYTES);
                tma_load_3d(sbase + SM_RING + s * STAGE_BYTES, &map_k, t * TILE, bar_full + s * 8, pol);
                tma_load_3d(sbase + SM_RING + s * STAGE_BYTES + TILE_BYTES, &map_v, t * TILE, bar_full + s * 8, pol);
                if (++s == STAGES) { s = 0; ph ^= 1; }
            }
            mbar_wait(bar_empty + s * 8, ph);
            tile_id[s] = -1;
            mbar_arrive(bar_full + s * 8);
        }
        __syncwarp();
    } else {
        float* sx = (float*)(smem + SM_X);
        float* sred = (float*)(smem + SM_RED);
        bool first = true;
        for (int slice = cta; slice < NSLICE || first; slice += nc) {
            const bool have = slice < NSLICE;
            uint4 w[9];
            const int r0 = warp * 8 + (lane >> 2);
            if (have) {
                const uint4* wp = (const uint4*)(wq + (size_t)r0 * QN + slice * 32 + (lane & 3) * 8);
#pragma unroll
                for (int i = 0; i < 9; i++) w[i] = __ldg(wp + (size_t)i * 64 * QN / 8);
            }
            if (first) {
                for (int i = tid; i < BATCH * DM; i += NWORK * 32) sx[i] = __bfloat162float(x[i]);
                named_bar(0, NTHREADS);
                first = false;
            }
            if (!have) break;
            float a0[8], a1[8];
#pragma unroll
            for (int j = 0; j < 8; j++) a0[j] = a1[j] = 0.f;
#pragma unroll
            for (int i = 0; i < 9; i++) {
                const float x0 = sx[r0 + 64 * i], x1 = sx[DM + r0 + 64 * i];
                const uint32_t u[4] = {w[i].x, w[i].y, w[i].z, w[i].w};
#pragma unroll
                for (int j = 0; j < 4; j++) {
                    const float lo = bf_lo(u[j]), hi = bf_hi(u[j]);
                    a0[2 * j] = fmaf(x0, lo, a0[2 * j]);
                    a0[2 * j + 1] = fmaf(x0, hi, a0[2 * j + 1]);
                    a1[2 * j] = fmaf(x1, lo, a1[2 * j]);
                    a1[2 * j + 1] = fmaf(x1, hi, a1[2 * j + 1]);
                }
            }
#pragma unroll
            for (int j = 0; j < 8; j++) {
#pragma unroll
                for (int o = 4; o < 32; o <<= 1) {
                    a0[j] += __shfl_xor_sync(0xffffffffu, a0[j], o);
                    a1[j] += __shfl_xor_sync(0xffffffffu, a1[j], o);
                }
            }
            if (lane < 4) {
#pragma unroll
                for (int j = 0; j < 8; j++) {
                    sred[warp * 64 + lane * 8 + j] = a0[j];
                    sred[warp * 64 + 32 + lane * 8 + j] = a1[j];
                }
            }
            named_bar(1, NWORK * 32);
            if (tid < 64) {
                float s = 0.f;
#pragma unroll
                for (int wv = 0; wv < NWORK; wv++) s += sred[wv * 64 + tid];
                g_q[(tid >> 5) * QN + slice * 32 + (tid & 31)] = __float2bfloat16(s);
                __threadfence();
            }
            named_bar(1, NWORK * 32);
            if (tid == 0) atomicAdd(&g_q_ready, 1u);
        }
        if (tid == 0) {
            unsigned v;
            for (uint32_t it = 0;; it++) {
                asm volatile("ld.acquire.gpu.global.u32 %0, [%1];" : "=r"(v) : "l"(&g_q_ready) : "memory");
                if (v >= (unsigned)NSLICE) break;
                if (it > (1u << 22)) __trap();
            }
        }
        named_bar(1, NWORK * 32);
        {
            const uint4* gq = (const uint4*)g_q;
            uint4* sq = (uint4*)(smem + SM_Q);
#pragma unroll
            for (int i = 0; i < 4; i++) sq[tid + i * 256] = __ldcg(gq + tid + i * 256);
        }
        named_bar(1, NWORK * 32);

        if (warp < NCW) {
            const int g8 = lane >> 2, t4 = lane & 3;
            const float SCALE = 0.08838834764831845f * 1.4426950408889634f;
            float acc[8][4];
            uint32_t qf[8][2];
            float m_run = -INFINITY, l_run = 0.f;
            int cur_g = -1, next_g = 0, fl = 0;
            const int krow = warp * 16 + (lane & 7);
            const int kch = lane >> 3;
            const int vrow = warp * 16 + ((lane >> 4) << 3) + (lane & 7);
            const int vch = (lane >> 3) & 1;
            float* spart = (float*)(smem + SM_PART);
            float* sml = (float*)(smem + SM_ML);
            const int ctid = tid;

            int s = 0;
            uint32_t ph = 0;
            while (true) {
                mbar_wait(bar_full + s * 8, ph);
                const int t = tile_id[s];
                const int g = (t < 0) ? NG : (t / TILES_PER_G);
                if (g != cur_g) {
                    if (cur_g >= 0) {
                        float* pp = spart + (fl * NCW + warp) * 2 * DH;
                        float* pm = sml + (fl * NCW + warp) * 4;
                        float l = l_run;
                        l += __shfl_xor_sync(0xffffffffu, l, 1);
                        l += __shfl_xor_sync(0xffffffffu, l, 2);
                        if (t4 == 0) {
#pragma unroll
                            for (int mt = 0; mt < 8; mt++) {
                                pp[mt * 16 + g8] = acc[mt][0];
                                pp[DH + mt * 16 + g8] = acc[mt][1];
                                pp[mt * 16 + g8 + 8] = acc[mt][2];
                                pp[DH + mt * 16 + g8 + 8] = acc[mt][3];
                            }
                            if (g8 < 2) { pm[g8 * 2] = m_run; pm[g8 * 2 + 1] = l; }
                        }
                        named_bar(2, NCW * 32);
                        const float* bp = spart + fl * NCW * 2 * DH;
                        const float* bm = sml + fl * NCW * 4;
#pragma unroll
                        for (int idx = ctid; idx < 2 * DH; idx += NCW * 32) {
                            const int sub = idx >> 7;
                            float M = bm[sub * 2];
#pragma unroll
                            for (int wv = 1; wv < NCW; wv++) M = fmaxf(M, bm[wv * 4 + sub * 2]);
                            float o = 0.f, L = 0.f;
#pragma unroll
                            for (int wv = 0; wv < NCW; wv++) {
                                const float e = ex2(bm[wv * 4 + sub * 2] - M);
                                o = fmaf(e, bp[wv * 2 * DH + idx], o);
                                L = fmaf(e, bm[wv * 4 + sub * 2 + 1], L);
                            }
                            float* rp = g_rec + ((size_t)(cur_g * 8 + (idx >> 5)) * MAX_CTAS + cta) * REC_W;
                            __stcg(rp + lane, nz(o));
                            if (lane < 4) __stcg(rp + 32 + lane, lane == 0 ? nz(M) : (lane == 1 ? nz(L) : 1.0f));
                        }
                        fl ^= 1;
                        next_g = cur_g + 1;
                    }
                    for (; next_g < g; next_g++) {
                        for (int idx = ctid; idx < 2 * DH; idx += NCW * 32) {
                            float* rp = g_rec + ((size_t)(next_g * 8 + (idx >> 5)) * MAX_CTAS + cta) * REC_W;
                            __stcg(rp + lane, -0.0f);
                            if (lane < 4) __stcg(rp + 32 + lane, lane == 0 ? -INFINITY : (lane == 1 ? -0.0f : 1.0f));
                        }
                    }
                    if (t < 0) break;
                    cur_g = g;
                    const uint32_t* sq32 =
                        (const uint32_t*)(smem + SM_Q) + ((g >> 4) * QN + ((g & 15) * 2 + (g8 & 1)) * DH) / 2;
#pragma unroll
                    for (int ks = 0; ks < 8; ks++) {
                        const uint32_t v0 = sq32[ks * 8 + t4], v1 = sq32[ks * 8 + 4 + t4];
                        qf[ks][0] = (g8 < 2) ? v0 : 0u;
                        qf[ks][1] = (g8 < 2) ? v1 : 0u;
                    }
#pragma unroll
                    for (int mt = 0; mt < 8; mt++) acc[mt][0] = acc[mt][1] = acc[mt][2] = acc[mt][3] = 0.f;
                    m_run = -INFINITY;
                    l_run = 0.f;
                }
                const uint32_t kb = sbase + SM_RING + s * STAGE_BYTES, vb = kb + TILE_BYTES;
                uint32_t kf[2][4][4], vf[8][4];
#pragma unroll
                for (int nt = 0; nt < 2; nt++)
#pragma unroll
                    for (int j = 0; j < 4; j++) {
                        const int row = krow + nt * 8;
                        const int ch = (j & 1) * 4 + kch;
                        ldsm_x4(kf[nt][j], kb + (j >> 1) * (TILE * 128) + row * 128 + ((ch ^ (row & 7)) << 4));
                    }
#pragma unroll
                for (int mt = 0; mt < 8; mt++) {
                    const int ch = (mt & 3) * 2 + vch;
                    ldsm_x4_t(vf[mt], vb + (mt >> 2) * (TILE * 128) + vrow * 128 + ((ch ^ (vrow & 7)) << 4));
                }
                __syncwarp();
                if (lane == 0) mbar_arrive(bar_empty + s * 8);
                if (++s == STAGES) { s = 0; ph ^= 1; }

                float sc[2][2][4];
#pragma unroll
                for (int nt = 0; nt < 2; nt++)
#pragma unroll
                    for (int hh = 0; hh < 2; hh++) {
                        sc[nt][hh][0] = sc[nt][hh][1] = sc[nt][hh][2] = sc[nt][hh][3] = 0.f;
#pragma unroll
                        for (int jj = 0; jj < 2; jj++) {
                            const int j = hh * 2 + jj;
                            mma_bf16(sc[nt][hh], qf[2 * j][0], 0u, qf[2 * j][1], 0u, kf[nt][j][0], kf[nt][j][1]);
                            mma_bf16(sc[nt][hh], qf[2 * j + 1][0], 0u, qf[2 * j + 1][1], 0u, kf[nt][j][2], kf[nt][j][3]);
                        }
                    }
                const float s0 = (sc[0][0][0] + sc[0][1][0]) * SCALE, s1 = (sc[0][0][1] + sc[0][1][1]) * SCALE;
                const float s2 = (sc[1][0][0] + sc[1][1][0]) * SCALE, s3 = (sc[1][0][1] + sc[1][1][1]) * SCALE;
                float mx = fmaxf(fmaxf(s0, s1), fmaxf(s2, s3));
                mx = fmaxf(mx, __shfl_xor_sync(0xffffffffu, mx, 1));
                mx = fmaxf(mx, __shfl_xor_sync(0xffffffffu, mx, 2));
                const float m_new = fmaxf(m_run, mx);
                const float alpha = ex2(m_run - m_new);
                m_run = m_new;
                const float p0 = ex2(s0 - m_new), p1 = ex2(s1 - m_new), p2 = ex2(s2 - m_new), p3 = ex2(s3 - m_new);
                l_run = fmaf(l_run, alpha, (p0 + p1) + (p2 + p3));
                const uint32_t pb0 = pack_bf16(p0, p1), pb1 = pack_bf16(p2, p3);
                const float al0 = __shfl_sync(0xffffffffu, alpha, 0), al1 = __shfl_sync(0xffffffffu, alpha, 4);
                if (al0 != 1.f || al1 != 1.f) {
#pragma unroll
                    for (int mt = 0; mt < 8; mt++) {
                        acc[mt][0] *= al0;
                        acc[mt][1] *= al1;
                        acc[mt][2] *= al0;
                        acc[mt][3] *= al1;
                    }
                }
#pragma unroll
                for (int mt = 0; mt < 8; mt++) mma_bf16(acc[mt], vf[mt][0], vf[mt][1], vf[mt][2], vf[mt][3], pb0, pb1);
            }
        }
    }
    __syncthreads();
    float* srec = (float*)(smem + SM_RING);
    float* sw = (float*)(smem + SM_W);
    float* so = (float*)(smem + SM_O);
    float* sred = (float*)(smem + SM_RED);
    for (int slice = cta; slice < NSLICE; slice += nc) {
        const int h = slice >> 2, s4 = slice & 3;
        const int n4 = nc * 9;
        {
            constexpr int MAXL = (2 * MAX_CTAS * 9 + NTHREADS - 1) / NTHREADS;
            uint4 v[MAXL];
#pragma unroll
            for (int k = 0; k < MAXL; k++) {
                const int i = tid + k * NTHREADS;
                if (i < 2 * n4) {
                    const int b = i >= n4, ii = i - b * n4;
                    const float* src = g_rec + (size_t)(((b * HKV + (h >> 1)) * 2 + (h & 1)) * 4 + s4) * MAX_CTAS * REC_W;
                    v[k] = ld_relaxed_v4(src + ii * 4);
                }
            }
#pragma unroll
            for (int k = 0; k < MAXL; k++) {
                const int i = tid + k * NTHREADS;
                if (i < 2 * n4) {
                    const int b = i >= n4, ii = i - b * n4;
                    float* src = g_rec + (size_t)(((b * HKV + (h >> 1)) * 2 + (h & 1)) * 4 + s4) * MAX_CTAS * REC_W;
                    uint32_t it = 0;
                    while (!all_nz(v[k])) {
                        v[k] = ld_relaxed_v4(src + ii * 4);
                        if (++it > (1u << 22)) __trap();
                    }
                    *(uint4*)(srec + b * MAX_CTAS * REC_W + ii * 4) = v[k];
                    __stcg((uint4*)(src + ii * 4), make_uint4(0u, 0u, 0u, 0u));
                }
            }
        }
        __syncthreads();
        if (slice == 0 && tid == 0) {
            g_tile_counter = 0u;
            g_q_ready = 0u;
        }
        if (warp < 2) {
            const float* rb = srec + warp * MAX_CTAS * REC_W;
            float M = -INFINITY;
            for (int c = lane; c < nc; c += 32) M = fmaxf(M, rb[c * REC_W + 32]);
#pragma unroll
            for (int o = 16; o > 0; o >>= 1) M = fmaxf(M, __shfl_xor_sync(0xffffffffu, M, o));
            float L = 0.f;
            for (int c = lane; c < nc; c += 32) {
                const float e = ex2(rb[c * REC_W + 32] - M);
                sw[warp * MAX_CTAS + c] = e;
                L = fmaf(e, rb[c * REC_W + 33], L);
            }
#pragma unroll
            for (int o = 16; o > 0; o >>= 1) L += __shfl_xor_sync(0xffffffffu, L, o);
            const float inv = 1.0f / L;
            for (int c = lane; c < nc; c += 32) sw[warp * MAX_CTAS + c] *= inv;
        }
        __syncthreads();
        if (warp < 8) {
            const int b = warp >> 2, part = warp & 3;
            const float* rb = srec + b * MAX_CTAS * REC_W;
            float o = 0.f;
            for (int c = part; c < nc; c += 4) o = fmaf(sw[b * MAX_CTAS + c], rb[c * REC_W + lane], o);
            sred[warp * 32 + lane] = o;
        }
        __syncthreads();
        if (tid < 64) {
            const int b = tid >> 5;
            const float o = (sred[(b * 4) * 32 + lane] + sred[(b * 4 + 1) * 32 + lane]) +
                            (sred[(b * 4 + 2) * 32 + lane] + sred[(b * 4 + 3) * 32 + lane]);
            so[tid] = __bfloat162float(__float2bfloat16(o));
        }
        if (slice == cta) mbar_wait(bar_wo, 0);
        __syncthreads();
        {
            const uint32_t* wp = (slice == cta) ? (const uint32_t*)(smem + SM_WO)
                                                : (const uint32_t*)((const uint8_t*)wo + (size_t)slice * WO_SLICE_BYTES);
            float y00 = 0.f, y01 = 0.f, y10 = 0.f, y11 = 0.f;
#pragma unroll 8
            for (int r = 0; r < 32; r++) {
                const uint32_t u = wp[r * (DM / 2) + tid];
                const float lo = bf_lo(u), hi = bf_hi(u);
                const float o0 = so[r], o1 = so[32 + r];
                y00 = fmaf(o0, lo, y00);
                y01 = fmaf(o0, hi, y01);
                y10 = fmaf(o1, lo, y10);
                y11 = fmaf(o1, hi, y11);
            }
            const int f0 = 2 * tid, f1 = DM + 2 * tid;
            __stcg(g_pout + ((f0 / 9) * NSLICE + slice) * 9 + f0 % 9, nz(y00));
            __stcg(g_pout + (((f0 + 1) / 9) * NSLICE + slice) * 9 + (f0 + 1) % 9, nz(y01));
            __stcg(g_pout + ((f1 / 9) * NSLICE + slice) * 9 + f1 % 9, nz(y10));
            __stcg(g_pout + (((f1 + 1) / 9) * NSLICE + slice) * 9 + (f1 + 1) % 9, nz(y11));
        }
        __syncthreads();
    }
    for (int u = cta; u < NSLICE; u += nc) {
        float* src = g_pout + (size_t)u * NSLICE * 9 + tid * 4;
        uint4 v = ld_relaxed_v4(src);
        uint32_t it = 0;
        while (!all_nz(v)) {
            v = ld_relaxed_v4(src);
            if (++it > (1u << 22)) __trap();
        }
        *(uint4*)(srec + tid * 4) = v;
        __stcg((uint4*)src, make_uint4(0u, 0u, 0u, 0u));
        __syncthreads();
        {
            float a = (srec[lane * 9 + warp] + srec[(lane + 32) * 9 + warp]) +
                      (srec[(lane + 64) * 9 + warp] + srec[(lane + 96) * 9 + warp]);
#pragma unroll
            for (int o = 16; o > 0; o >>= 1) a += __shfl_xor_sync(0xffffffffu, a, o);
            if (lane == 0) out[u * 9 + warp] = __float2bfloat16(a);
        }
        __syncthreads();
    }
}

typedef CUresult (*EncodeTiledFn)(CUtensorMap*, CUtensorMapDataType, cuuint32_t, void*, const cuuint64_t*,
                                  const cuuint64_t*, const cuuint32_t*, const cuuint32_t*, CUtensorMapInterleave,
                                  CUtensorMapSwizzle, CUtensorMapL2promotion, CUtensorMapFloatOOBfill);

}

extern "C" void kernel_launch(void* const* d_in, const int* in_sizes, int n_in, void* d_out, int out_size) {
    (void)in_sizes; (void)n_in; (void)out_size;
    const __nv_bfloat16* x = (const __nv_bfloat16*)d_in[0];
    void* kc = d_in[1];
    void* vc = d_in[2];
    const __nv_bfloat16* wq = (const __nv_bfloat16*)d_in[3];
    const __nv_bfloat16* wo = (const __nv_bfloat16*)d_in[4];

    static EncodeTiledFn enc = nullptr;
    static int num_sms = 0;
    if (!enc) {
        cudaDriverEntryPointQueryResult qr;
        cudaGetDriverEntryPoint("cuTensorMapEncodeTiled", (void**)&enc, cudaEnableDefault, &qr);
        int dev = 0;
        cudaGetDevice(&dev);
        cudaDeviceGetAttribute(&num_sms, cudaDevAttrMultiProcessorCount, dev);
        cudaFuncSetAttribute(gqa_decode_kernel, cudaFuncAttributeMaxDynamicSharedMemorySize, SMEM_BYTES);
    }
    CUtensorMap mk, mv;
    cuuint64_t gd[3] = {64, (cuuint64_t)NG * SK, 2};
    cuuint64_t gs[2] = {256, 128};
    cuuint32_t box[3] = {64, TILE, 2};
    cuuint32_t es[3] = {1, 1, 1};
    enc(&mk, CU_TENSOR_MAP_DATA_TYPE_BFLOAT16, 3, kc, gd, gs, box, es, CU_TENSOR_MAP_INTERLEAVE_NONE,
        CU_TENSOR_MAP_SWIZZLE_128B, CU_TENSOR_MAP_L2_PROMOTION_L2_256B, CU_TENSOR_MAP_FLOAT_OOB_FILL_NONE);
    enc(&mv, CU_TENSOR_MAP_DATA_TYPE_BFLOAT16, 3, vc, gd, gs, box, es, CU_TENSOR_MAP_INTERLEAVE_NONE,
        CU_TENSOR_MAP_SWIZZLE_128B, CU_TENSOR_MAP_L2_PROMOTION_L2_256B, CU_TENSOR_MAP_FLOAT_OOB_FILL_NONE);
    int grid = num_sms < MAX_CTAS ? num_sms : MAX_CTAS;
    gqa_decode_kernel<<<grid, NTHREADS, SMEM_BYTES>>>(mk, mv, x, wq, wo, (__nv_bfloat16*)d_out);
}
```

```cpp
#include <cuda_runtime.h>
#include <cuda.h>
#include <cuda_bf16.h>
#include <stdint.h>

namespace {

constexpr int BATCH = 2, DM = 576, HQ = 32, HKV = 16, SK = 32768, DH = 128;
constexpr int NG = BATCH * HKV;
constexpr int QN = HQ * DH;
#define TILE_KEYS 64
#define NSTAGES 4
#define NINFLIGHT 2
#define WOLEAD 0
constexpr int WO_LEAD = WOLEAD;
constexpr int TILE = TILE_KEYS;
constexpr int NCW = TILE / 16;
constexpr int STAGES = NSTAGES;
constexpr int INFLIGHT = NINFLIGHT;
constexpr int TILE_BYTES = TILE * DH * 2;
constexpr int STAGE_BYTES = 2 * TILE_BYTES;
constexpr int TILES_PER_G = SK / TILE;
constexpr int NTILES = NG * TILES_PER_G;
constexpr int NHW = 9;
constexpr int NHT = NHW * 32;
constexpr int NCT = NCW * 32;
constexpr int NTHREADS = NCT + 32 + NHT;
constexpr int NSLICE = 128;
constexpr int MAX_CTAS = 160;
constexpr int REC_W = 36;
constexpr int NUNIT = BATCH * DM / 16;
constexpr int WO_PITCH = DM * 2 + 16;

constexpr int SM_RING = 0;
constexpr int WO_BYTES = 32 * WO_PITCH;
constexpr int SM_WO = SM_RING + STAGES * STAGE_BYTES;
constexpr int SM_Q = SM_WO + WO_BYTES;
constexpr int SM_PART = SM_Q + BATCH * QN * 2;
constexpr int SM_ML = SM_PART + 2 * NCW * 2 * DH * 4;
constexpr int SM_HB = SM_ML + 2 * NCW * 4 * 4;
constexpr int SM_HM = SM_HB + NSLICE * 20 * 4;
constexpr int SM_HR = SM_HM + 2 * MAX_CTAS * 4;
constexpr int SM_HO = SM_HR + NHW * 64 * 4;
constexpr int SM_BAR = SM_HO + NHW * 64 * 4;
constexpr int SM_TID = SM_BAR + (2 * STAGES + 3 + NG) * 8;
constexpr int SM_TOTAL = SM_TID + STAGES * 4;
constexpr int SMEM_BYTES = SM_TOTAL;
static_assert(SMEM_BYTES <= 232448, "too much shared memory");
static_assert(INFLIGHT <= STAGES, "inflight");

#define DBG(e) do {} while (0)
#define DBGT(e) do {} while (0)
__device__ unsigned int g_tile_counter;
__device__ __align__(16) uint32_t g_q[BATCH * QN / 2];
__device__ __align__(16) float g_rec[NG * 2 * 4 * MAX_CTAS * REC_W];
__device__ __align__(16) float g_pout[BATCH * NSLICE * DM];

__device__ __forceinline__ uint32_t smem_u32(const void* p) { return (uint32_t)__cvta_generic_to_shared(p); }
__device__ __forceinline__ void mbar_init(uint32_t bar, uint32_t cnt) {
    asm volatile("mbarrier.init.shared::cta.b64 [%0], %1;" ::"r"(bar), "r"(cnt));
}
__device__ __forceinline__ void mbar_expect_tx(uint32_t bar, uint32_t bytes) {
    asm volatile("mbarrier.arrive.expect_tx.shared::cta.b64 _, [%0], %1;" ::"r"(bar), "r"(bytes) : "memory");
}
__device__ __forceinline__ void mbar_arrive(uint32_t bar) {
    asm volatile("mbarrier.arrive.shared::cta.b64 _, [%0];" ::"r"(bar) : "memory");
}
__device__ __forceinline__ void mbar_wait(uint32_t bar, uint32_t parity) {
    uint32_t done;
    for (uint32_t it = 0;; it++) {
        asm volatile(
            "{\n.reg .pred p;\n"
            "mbarrier.try_wait.parity.shared::cta.b64 p, [%1], %2;\n"
            "selp.u32 %0, 1, 0, p;\n}\n"
            : "=r"(done)
            : "r"(bar), "r"(parity)
            : "memory");
        if (done) break;
        if (it > (1u << 26)) __trap();
    }
}
__device__ __forceinline__ void tma_load_3d(uint32_t dst, const CUtensorMap* m, int row, uint32_t bar, uint64_t pol) {
    asm volatile(
        "cp.async.bulk.tensor.3d.shared::cluster.global.mbarrier::complete_tx::bytes.L2::cache_hint "
        "[%0], [%1, {%3, %4, %5}], [%2], %6;" ::"r"(dst),
        "l"((uint64_t)m), "r"(bar), "r"(0), "r"(row), "r"(0), "l"(pol)
        : "memory");
}
__device__ __forceinline__ void bulk_load(uint32_t dst, const void* src, uint32_t bytes, uint32_t bar) {
    asm volatile("cp.async.bulk.shared::cluster.global.mbarrier::complete_tx::bytes [%0], [%1], %2, [%3];" ::"r"(dst),
                 "l"(src), "r"(bytes), "r"(bar)
                 : "memory");
}
__device__ __forceinline__ void ldsm_x4(uint32_t (&r)[4], uint32_t addr) {
    asm volatile("ldmatrix.sync.aligned.m8n8.x4.shared.b16 {%0,%1,%2,%3}, [%4];"
                 : "=r"(r[0]), "=r"(r[1]), "=r"(r[2]), "=r"(r[3])
                 : "r"(addr)
                 : "memory");
}
__device__ __forceinline__ void ldsm_x4_t(uint32_t (&r)[4], uint32_t addr) {
    asm volatile("ldmatrix.sync.aligned.m8n8.x4.trans.shared.b16 {%0,%1,%2,%3}, [%4];"
                 : "=r"(r[0]), "=r"(r[1]), "=r"(r[2]), "=r"(r[3])
                 : "r"(addr)
                 : "memory");
}
__device__ __forceinline__ void mma_bf16(float (&c)[4], uint32_t a0, uint32_t a1, uint32_t a2, uint32_t a3, uint32_t b0,
                                         uint32_t b1) {
    asm volatile(
        "mma.sync.aligned.m16n8k16.row.col.f32.bf16.bf16.f32 {%0,%1,%2,%3}, {%4,%5,%6,%7}, {%8,%9}, {%0,%1,%2,%3};"
        : "+f"(c[0]), "+f"(c[1]), "+f"(c[2]), "+f"(c[3])
        : "r"(a0), "r"(a1), "r"(a2), "r"(a3), "r"(b0), "r"(b1));
}
__device__ __forceinline__ float ex2(float x) {
    float y;
    asm("ex2.approx.ftz.f32 %0, %1;" : "=f"(y) : "f"(x));
    return y;
}
__device__ __forceinline__ uint32_t pack_bf16(float lo, float hi) {
    uint32_t r;
    asm("cvt.rn.bf16x2.f32 %0, %1, %2;" : "=r"(r) : "f"(hi), "f"(lo));
    return r;
}
__device__ __forceinline__ void bar_sync(int id, int n) { asm volatile("bar.sync %0, %1;" ::"r"(id), "r"(n) : "memory"); }
__device__ __forceinline__ void bar_arrive(int id, int n) { asm volatile("bar.arrive %0, %1;" ::"r"(id), "r"(n) : "memory"); }
__device__ __forceinline__ float nz(float v) { return (__float_as_uint(v) == 0u) ? __uint_as_float(0x80000000u) : v; }
__device__ __forceinline__ uint4 ld_relaxed_v4(const void* p) {
    uint4 v;
    asm volatile("ld.relaxed.gpu.global.v4.u32 {%0,%1,%2,%3}, [%4];"
                 : "=r"(v.x), "=r"(v.y), "=r"(v.z), "=r"(v.w)
                 : "l"(p)
                 : "memory");
    return v;
}
__device__ __forceinline__ bool all_nz(const uint4& v) { return v.x != 0u && v.y != 0u && v.z != 0u && v.w != 0u; }
__device__ __forceinline__ uint4 poll_v4(const void* p, uint4 v) {
    uint32_t it = 0;
    while (!all_nz(v)) {
        v = ld_relaxed_v4(p);
        if (++it > (1u << 22)) __trap();
    }
    return v;
}
__device__ __forceinline__ float bf_lo(uint32_t u) { return __uint_as_float(u << 16); }
__device__ __forceinline__ float bf_hi(uint32_t u) { return __uint_as_float(u & 0xffff0000u); }

enum { BAR_CONS = 1, BAR_HELP = 2 };

__global__ void __launch_bounds__(NTHREADS, 1)
gqa_decode_kernel(const __grid_constant__ CUtensorMap map_k, const __grid_constant__ CUtensorMap map_v,
                  const __nv_bfloat16* __restrict__ x, const __nv_bfloat16* __restrict__ wq,
                  const __nv_bfloat16* __restrict__ wo, __nv_bfloat16* __restrict__ out) {
    extern __shared__ __align__(1024) uint8_t smem[];
    const uint32_t sbase = smem_u32(smem);
    if (sbase & 1023u) __trap();
    const int tid = threadIdx.x, warp = tid >> 5, lane = tid & 31;
    const int nc = gridDim.x, cta = blockIdx.x;
    const uint32_t bar_full = sbase + SM_BAR, bar_empty = bar_full + STAGES * 8, bar_sig = bar_full + 2 * STAGES * 8;
    const uint32_t bar_q = bar_sig + 3 * 8;
    volatile int* tile_id = (volatile int*)(smem + SM_TID);

    if (warp == NCW) {
        if (lane == 0) {
            DBG(0);
            DBGT(28);
            for (int s = 0; s < STAGES; s++) {
                mbar_init(bar_full + s * 8, 1);
                mbar_init(bar_empty + s * 8, NCW);
            }
            mbar_init(bar_sig, NCW);
            mbar_init(bar_sig + 8, NCW);
            mbar_init(bar_sig + 16, 1);
            for (int g = 0; g < NG; g++) mbar_init(bar_q + g * 8, 1);
            asm volatile("fence.mbarrier_init.release.cluster;" ::: "memory");
            asm volatile("fence.proxy.async.shared::cta;" ::: "memory");
        }
        __syncwarp();
        __syncthreads();
        if (lane == 0) {
            uint64_t pol;
            asm volatile("createpolicy.fractional.L2::evict_first.b64 %0, 1.0;" : "=l"(pol));
            constexpr int NSTATIC = 2;
            int t = cta, tn = cta + nc;
            int s = 0, s2 = 0;
            uint32_t ph = 1, ph2 = 0;
            const int dyn_base = NSTATIC * nc;
            bool wo_todo = cta < NSLICE;
            for (int n = 0;; n++) {
                if (wo_todo && t >= NTILES - WO_LEAD * nc) {
                    wo_todo = false;
                    mbar_expect_tx(bar_sig + 16, 32 * DM * 2);
                    for (int r = 0; r < 32; r++)
                        bulk_load(sbase + SM_WO + r * WO_PITCH, wo + (size_t)(cta * 32 + r) * DM, DM * 2, bar_sig + 16);
                }
                if (t >= NTILES) break;
                int tnn = dyn_base + (int)atomicAdd(&g_tile_counter, 1u);
                if (n >= INFLIGHT) {
                    mbar_wait(bar_full + s2 * 8, ph2);
                    if (++s2 == STAGES) { s2 = 0; ph2 ^= 1; }
                }
                mbar_wait(bar_empty + s * 8, ph);
                tile_id[s] = t;
                mbar_expect_tx(bar_full + s * 8, STAGE_BYTES);
                tma_load_3d(sbase + SM_RING + s * STAGE_BYTES, &map_k, t * TILE, bar_full + s * 8, pol);
                tma_load_3d(sbase + SM_RING + s * STAGE_BYTES + TILE_BYTES, &map_v, t * TILE, bar_full + s * 8, pol);
                if (++s == STAGES) { s = 0; ph ^= 1; }
                t = tn;
                tn = tnn;
            }
            mbar_wait(bar_empty + s * 8, ph);
            tile_id[s] = -1;
            mbar_arrive(bar_full + s * 8);
            DBG(11);
        }
    } else if (warp < NCW) {
        __syncthreads();
        if (tid == 0) DBG(3);
        const int g8 = lane >> 2, t4 = lane & 3;
        const float SCALE = 0.08838834764831845f * 1.4426950408889634f;
        float acc[8][4];
        uint32_t qf[8][2];
        float m_run = -INFINITY, l_run = 0.f;
        int cur_g = -1, next_g = 0, fl = 0;
        bool sig0 = false;
        const int krow = warp * 16 + (lane & 7);
        const int kch = lane >> 3;
        const int vrow = warp * 16 + ((lane >> 4) << 3) + (lane & 7);
        const int vch = (lane >> 3) & 1;
        float* spart = (float*)(smem + SM_PART);
        float* sml = (float*)(smem + SM_ML);

        int s = 0;
        uint32_t ph = 0;
        while (true) {
            mbar_wait(bar_full + s * 8, ph);
            const int t = tile_id[s];
            const int g = (t < 0) ? NG : (t / TILES_PER_G);
            if (tid == 0 && cur_g < 0) DBG(4);
            if (tid == 0 && t < 0) DBG(5);
            if (g != cur_g) {
                if (cur_g >= 0) {
                    float* pp = spart + (fl * NCW + warp) * 2 * DH;
                    float* pm = sml + (fl * NCW + warp) * 4;
                    float l = l_run;
                    l += __shfl_xor_sync(0xffffffffu, l, 1);
                    l += __shfl_xor_sync(0xffffffffu, l, 2);
                    if (t4 == 0) {
#pragma unroll
                        for (int mt = 0; mt < 8; mt++) {
                            *(float2*)(pp + (mt * 16 + g8) * 2) = make_float2(acc[mt][0], acc[mt][1]);
                            *(float2*)(pp + (mt * 16 + g8 + 8) * 2) = make_float2(acc[mt][2], acc[mt][3]);
                        }
                        if (g8 < 2) *(float2*)(pm + g8 * 2) = make_float2(m_run, l);
                    }
                    bar_sync(BAR_CONS, NCT);
                    const float* bp = spart + fl * NCW * 2 * DH;
                    const float* bm = sml + fl * NCW * 4;
                    float4 ml[NCW];
#pragma unroll
                    for (int wv = 0; wv < NCW; wv++) ml[wv] = *(const float4*)(bm + wv * 4);
                    float M0 = ml[0].x, M1 = ml[0].z;
#pragma unroll
                    for (int wv = 1; wv < NCW; wv++) { M0 = fmaxf(M0, ml[wv].x); M1 = fmaxf(M1, ml[wv].z); }
                    float L0 = 0.f, L1 = 0.f;
#pragma unroll
                    for (int wv = 0; wv < NCW; wv++) {
                        ml[wv].x = ex2(ml[wv].x - M0);
                        ml[wv].z = ex2(ml[wv].z - M1);
                        L0 = fmaf(ml[wv].x, ml[wv].y, L0);
                        L1 = fmaf(ml[wv].z, ml[wv].w, L1);
                    }
#pragma unroll
                    for (int d = tid; d < DH; d += NCT) {
                        float o0 = 0.f, o1 = 0.f;
#pragma unroll
                        for (int wv = 0; wv < NCW; wv++) {
                            const float2 f = *(const float2*)(bp + wv * 2 * DH + d * 2);
                            o0 = fmaf(ml[wv].x, f.x, o0);
                            o1 = fmaf(ml[wv].z, f.y, o1);
                        }
                        float* rp = g_rec + ((size_t)(cur_g * 8 + (d >> 5)) * MAX_CTAS + cta) * REC_W;
                        __stcg(rp + lane, nz(o0));
                        __stcg(rp + 4 * MAX_CTAS * REC_W + lane, nz(o1));
                        if (lane < 2) {
                            const float4 f = make_float4(nz(lane ? M1 : M0), nz(lane ? L1 : L0), 1.f, 1.f);
                            __stcg((float4*)(rp + lane * 4 * MAX_CTAS * REC_W + 32), f);
                        }
                    }
                    fl ^= 1;
                    next_g = cur_g + 1;
                }
                for (; next_g < g; next_g++) {
                    mbar_wait(bar_q + next_g * 8, 0);
                    for (int idx = tid; idx < 2 * DH; idx += NCT) {
                        float* rp = g_rec + ((size_t)(next_g * 8 + (idx >> 5)) * MAX_CTAS + cta) * REC_W;
                        __stcg(rp + lane, -0.0f);
                        if (lane < 4) __stcg(rp + 32 + lane, lane == 0 ? -INFINITY : (lane == 1 ? -0.0f : 1.0f));
                    }
                }
                if (!sig0 && g >= HKV) { if (lane == 0) mbar_arrive(bar_sig); sig0 = true; }
                if (t < 0) break;
                cur_g = g;
                mbar_wait(bar_q + g * 8, 0);
                const uint32_t* sq32 =
                    (const uint32_t*)(smem + SM_Q) + ((g >> 4) * QN + ((g & 15) * 2 + (g8 & 1)) * DH) / 2;
#pragma unroll
                for (int ks = 0; ks < 8; ks++) {
                    const uint32_t v0 = sq32[ks * 8 + t4], v1 = sq32[ks * 8 + 4 + t4];
                    qf[ks][0] = (g8 < 2) ? v0 : 0u;
                    qf[ks][1] = (g8 < 2) ? v1 : 0u;
                }
#pragma unroll
                for (int mt = 0; mt < 8; mt++) acc[mt][0] = acc[mt][1] = acc[mt][2] = acc[mt][3] = 0.f;
                m_run = -INFINITY;
                l_run = 0.f;
            }
            const uint32_t kb = sbase + SM_RING + s * STAGE_BYTES, vb = kb + TILE_BYTES;
            uint32_t kf[2][4][4], vf[8][4];
#pragma unroll
            for (int nt = 0; nt < 2; nt++)
#pragma unroll
                for (int j = 0; j < 4; j++) {
                    const int row = krow + nt * 8;
                    const int ch = (j & 1) * 4 + kch;
                    ldsm_x4(kf[nt][j], kb + (j >> 1) * (TILE * 128) + row * 128 + ((ch ^ (row & 7)) << 4));
                }
#pragma unroll
            for (int mt = 0; mt < 8; mt++) {
                const int ch = (mt & 3) * 2 + vch;
                ldsm_x4_t(vf[mt], vb + (mt >> 2) * (TILE * 128) + vrow * 128 + ((ch ^ (vrow & 7)) << 4));
            }
            __syncwarp();
            if (lane == 0) mbar_arrive(bar_empty + s * 8);
            if (++s == STAGES) { s = 0; ph ^= 1; }

            float sc[2][2][4];
#pragma unroll
            for (int nt = 0; nt < 2; nt++)
#pragma unroll
                for (int hh = 0; hh < 2; hh++) {
                    sc[nt][hh][0] = sc[nt][hh][1] = sc[nt][hh][2] = sc[nt][hh][3] = 0.f;
#pragma unroll
                    for (int jj = 0; jj < 2; jj++) {
                        const int j = hh * 2 + jj;
                        mma_bf16(sc[nt][hh], qf[2 * j][0], 0u, qf[2 * j][1], 0u, kf[nt][j][0], kf[nt][j][1]);
                        mma_bf16(sc[nt][hh], qf[2 * j + 1][0], 0u, qf[2 * j + 1][1], 0u, kf[nt][j][2], kf[nt][j][3]);
                    }
                }
            const float s0 = (sc[0][0][0] + sc[0][1][0]) * SCALE, s1 = (sc[0][0][1] + sc[0][1][1]) * SCALE;
            const float s2 = (sc[1][0][0] + sc[1][1][0]) * SCALE, s3 = (sc[1][0][1] + sc[1][1][1]) * SCALE;
            float mx = fmaxf(fmaxf(s0, s1), fmaxf(s2, s3));
            mx = fmaxf(mx, __shfl_xor_sync(0xffffffffu, mx, 1));
            mx = fmaxf(mx, __shfl_xor_sync(0xffffffffu, mx, 2));
            const float m_new = fmaxf(m_run, mx);
            const float alpha = ex2(m_run - m_new);
            m_run = m_new;
            const float p0 = ex2(s0 - m_new), p1 = ex2(s1 - m_new), p2 = ex2(s2 - m_new), p3 = ex2(s3 - m_new);
            l_run = fmaf(l_run, alpha, (p0 + p1) + (p2 + p3));
            const uint32_t pb0 = pack_bf16(p0, p1), pb1 = pack_bf16(p2, p3);
            const float al0 = __shfl_sync(0xffffffffu, alpha, 0), al1 = __shfl_sync(0xffffffffu, alpha, 4);
            if (al0 != 1.f || al1 != 1.f) {
#pragma unroll
                for (int mt = 0; mt < 8; mt++) {
                    acc[mt][0] *= al0;
                    acc[mt][1] *= al1;
                    acc[mt][2] *= al0;
                    acc[mt][3] *= al1;
                }
            }
#pragma unroll
            for (int mt = 0; mt < 8; mt++) mma_bf16(acc[mt], vf[mt][0], vf[mt][1], vf[mt][2], vf[mt][3], pb0, pb1);
        }
        if (tid == 0) DBG(6);
        if (lane == 0) mbar_arrive(bar_sig + 8);
    } else {
        const int ht = tid - (NCT + 32), hw = ht >> 5;
        float* hb = (float*)(smem + SM_HB);
        float* hm = (float*)(smem + SM_HM);
        float* hr = (float*)(smem + SM_HR);
        {
            int slice = cta;
            const int r0 = hw * 8 + (lane >> 2);
            uint4 w[8];
            if (slice < NSLICE) {
                const uint4* wp = (const uint4*)(wq + (size_t)r0 * QN + slice * 32 + (lane & 3) * 8);
#pragma unroll
                for (int i = 0; i < 8; i++) w[i] = __ldg(wp + (size_t)i * 72 * QN / 8);
            }
            const uint32_t xv0 = ((const uint32_t*)x)[ht], xv1 = ((const uint32_t*)x)[NHT + ht];
            __syncthreads();
            *(float2*)(hb + 2 * ht) = make_float2(bf_lo(xv0), bf_hi(xv0));
            *(float2*)(hb + DM + 2 * ht) = make_float2(bf_lo(xv1), bf_hi(xv1));
            bar_sync(BAR_HELP, NHT);
            for (; slice < NSLICE;) {
                float a0[8], a1[8];
#pragma unroll
                for (int j = 0; j < 8; j++) a0[j] = a1[j] = 0.f;
#pragma unroll
                for (int i = 0; i < 8; i++) {
                    const float x0 = hb[r0 + 72 * i], x1 = hb[DM + r0 + 72 * i];
                    const uint32_t u[4] = {w[i].x, w[i].y, w[i].z, w[i].w};
#pragma unroll
                    for (int j = 0; j < 4; j++) {
                        const float lo = bf_lo(u[j]), hi = bf_hi(u[j]);
                        a0[2 * j] = fmaf(x0, lo, a0[2 * j]);
                        a0[2 * j + 1] = fmaf(x0, hi, a0[2 * j + 1]);
                        a1[2 * j] = fmaf(x1, lo, a1[2 * j]);
                        a1[2 * j + 1] = fmaf(x1, hi, a1[2 * j + 1]);
                    }
                }
#pragma unroll
                for (int j = 0; j < 8; j++) {
#pragma unroll
                    for (int o = 4; o < 32; o <<= 1) {
                        a0[j] += __shfl_xor_sync(0xffffffffu, a0[j], o);
                        a1[j] += __shfl_xor_sync(0xffffffffu, a1[j], o);
                    }
                }
                if (lane < 4) {
#pragma unroll
                    for (int j = 0; j < 8; j++) {
                        hr[hw * 64 + lane * 8 + j] = a0[j];
                        hr[hw * 64 + 32 + lane * 8 + j] = a1[j];
                    }
                }
                bar_sync(BAR_HELP, NHT);
                if (ht < 32) {
                    float s0 = 0.f, s1 = 0.f;
#pragma unroll
                    for (int wv = 0; wv < NHW; wv++) {
                        const float2 f = *(const float2*)(hr + wv * 64 + ht * 2);
                        s0 += f.x;
                        s1 += f.y;
                    }
                    uint32_t u = pack_bf16(s0, s1);
                    if (u == 0u) u = 0x80000000u;
                    __stcg(g_q + ((ht >> 4) * QN + slice * 32) / 2 + (ht & 15), u);
                    if (ht == 0) DBG(1);
                }
                slice += nc;
                if (slice < NSLICE) {
                    bar_sync(BAR_HELP, NHT);
                    const uint4* wp = (const uint4*)(wq + (size_t)r0 * QN + slice * 32 + (lane & 3) * 8);
#pragma unroll
                    for (int i = 0; i < 8; i++) w[i] = __ldg(wp + (size_t)i * 72 * QN / 8);
                }
            }
        }
        for (int g = hw; g < NG; g += NHW) {
            const uint4* src = (const uint4*)g_q + g * 32 + lane;
            uint4 v = ld_relaxed_v4(src);
            v = poll_v4(src, v);
            ((uint4*)(smem + SM_Q))[g * 32 + lane] = v;
            __syncwarp();
            if (lane == 0) mbar_arrive(bar_q + g * 8);
        }
        if (ht == 0) DBG(2);
        const int rr = ht / 9, part = ht - rr * 9;
        constexpr int MAXS = (NSLICE + 63) / 64;
        float o_b0[MAXS];
#pragma unroll 1
        for (int b = 0; b < BATCH; b++) {
            const bool live = (b == BATCH - 1);
            if (lane == 0) mbar_wait(bar_sig + b * 8, 0);
            __syncwarp();
            if (ht == 0) DBG(16 + b * 4);
            int si = 0;
#pragma unroll 1
            for (int slice = cta; slice < NSLICE; slice += nc, si++) {
                float* src = g_rec + (size_t)(b * HKV * 8 + slice) * MAX_CTAS * REC_W + ht * 4;
                constexpr int NR = MAX_CTAS / 32;
                uint4 v[NR];
#pragma unroll
                for (int k = 0; k < NR; k++) v[k] = (rr + 32 * k < nc) ? make_uint4(0u, 0u, 0u, 0u) : make_uint4(1u, 1u, 1u, 1u);
                for (uint32_t it = 0;; it++) {
#pragma unroll
                    for (int k = 0; k < NR; k++)
                        if (!all_nz(v[k])) v[k] = ld_relaxed_v4(src + k * NHT * 4);
                    bool ok = true;
#pragma unroll
                    for (int k = 0; k < NR; k++) ok = ok && all_nz(v[k]);
                    if (ok) break;
                    if (it > (1u << 22)) __trap();
                }
                if (part == 8) {
#pragma unroll
                    for (int k = 0; k < NR; k++)
                        if (rr + 32 * k < nc) {
                            hm[rr + 32 * k] = __uint_as_float(v[k].x);
                            hm[MAX_CTAS + rr + 32 * k] = __uint_as_float(v[k].y);
                        }
                }
                bar_sync(BAR_HELP, NHT);
                if (ht == 0) DBG(17 + b * 4);
                float M = -INFINITY;
#pragma unroll
                for (int k = 0; k < NR; k++)
                    if (lane + 32 * k < nc) M = fmaxf(M, hm[lane + 32 * k]);
#pragma unroll
                for (int o = 16; o > 0; o >>= 1) M = fmaxf(M, __shfl_xor_sync(0xffffffffu, M, o));
                float4 a = make_float4(0.f, 0.f, 0.f, 0.f);
#pragma unroll
                for (int k = 0; k < NR; k++)
                    if (rr + 32 * k < nc) {
                        const float e = ex2(hm[rr + 32 * k] - M);
                        a.x = fmaf(e, __uint_as_float(v[k].x), a.x);
                        a.y = fmaf(e, __uint_as_float(v[k].y), a.y);
                        a.z = fmaf(e, __uint_as_float(v[k].z), a.z);
                        a.w = fmaf(e, __uint_as_float(v[k].w), a.w);
                    }
                *(float4*)(hb + ht * 4) = a;
                if (ht == 0 && live) DBG(12);
                bar_sync(BAR_HELP, NHT);
                if (ht == 0 && live) DBG(13);
                float o0 = 0.f, o1 = 0.f, L = hb[lane * REC_W + 33];
#pragma unroll
                for (int r = 0; r < 32; r += 2) {
                    o0 += hb[r * REC_W + lane];
                    o1 += hb[(r + 1) * REC_W + lane];
                }
#pragma unroll
                for (int o = 16; o > 0; o >>= 1) L += __shfl_xor_sync(0xffffffffu, L, o);
                const float ob = __bfloat162float(__float2bfloat16((o0 + o1) / L));
                float oa = ob;
#pragma unroll
                for (int i = 0; i < MAXS; i++)
                    if (i == si) {
                        if (!live) o_b0[i] = ob;
                        oa = o_b0[i];
                    }
                if (ht == 0 && live) DBG(14);
                __nv_bfloat16* ho = (__nv_bfloat16*)(smem + SM_HO) + hw * 64;
                ho[lane] = __float2bfloat16(oa);
                ho[32 + lane] = __float2bfloat16(ob);
                if (si > 0) {
                    bar_sync(BAR_HELP, NHT);
                    const uint32_t* gw = (const uint32_t*)(wo + (size_t)slice * 32 * DM) + ht;
                    for (int r = 0; r < 32; r++) *(uint32_t*)(smem + SM_WO + r * WO_PITCH + ht * 4) = __ldg(gw + r * (DM / 2));
                    bar_sync(BAR_HELP, NHT);
                } else if (live) {
                    mbar_wait(bar_sig + 16, 0);
                }
                __syncwarp();
                {
                    const int g8 = lane >> 2, t4 = lane & 3;
                    const uint32_t* ho32 = (const uint32_t*)ho + (g8 & 1) * 16 + t4;
                    uint32_t bf[4];
#pragma unroll
                    for (int i = 0; i < 4; i++) bf[i] = (g8 < 2) ? ho32[i * 4] : 0u;
                    const uint32_t wa = sbase + SM_WO + (((lane >> 4) << 3) + (lane & 7)) * WO_PITCH +
                                        (hw * 64 + ((lane >> 3) & 1) * 8) * 2;
                    float* pw = g_pout + (size_t)slice * DM + hw * 64 + g8;
#pragma unroll
                    for (int mt = 0; mt < 4; mt++) {
                        uint32_t a0[4], a1[4];
                        ldsm_x4_t(a0, wa + mt * 32);
                        ldsm_x4_t(a1, wa + mt * 32 + 16 * WO_PITCH);
                        float c[4] = {0.f, 0.f, 0.f, 0.f};
                        mma_bf16(c, a0[0], a0[1], a0[2], a0[3], bf[0], bf[1]);
                        mma_bf16(c, a1[0], a1[1], a1[2], a1[3], bf[2], bf[3]);
                        if (live && t4 == 0) {
                            __stcg(pw + NSLICE * DM + mt * 16, nz(c[1]));
                            __stcg(pw + NSLICE * DM + mt * 16 + 8, nz(c[3]));
                            __stcg(pw + mt * 16, nz(c[0]));
                            __stcg(pw + mt * 16 + 8, nz(c[2]));
                        }
                    }
                }
                if (ht == 0) DBG(18 + b * 4);
#pragma unroll
                for (int k = 0; k < NR; k++)
                    if (rr + 32 * k < nc) __stcg((uint4*)(src + k * NHT * 4), make_uint4(0u, 0u, 0u, 0u));
                if (live) {
                    if (ht < 32) __stcg(g_q + ((ht >> 4) * QN + slice * 32) / 2 + (ht & 15), 0u);
                    if (slice == NSLICE - 1 && ht == 0) g_tile_counter = 0u;
                }
                bar_sync(BAR_HELP, NHT);
            }
#pragma unroll 1
            for (int u = cta; u < NUNIT; u += nc) {
                if (ht < 2 * NSLICE) {
                    const int ub = u / (NUNIT / 2), uc = u - ub * (NUNIT / 2);
                    float* src = g_pout + (size_t)(ub * NSLICE + (ht >> 1)) * DM + uc * 16 + (ht & 1) * 8;
                    uint4 v0 = make_uint4(0u, 0u, 0u, 0u), v1 = v0;
                    for (uint32_t it = 0;; it++) {
                        if (!all_nz(v0)) v0 = ld_relaxed_v4(src);
                        if (!all_nz(v1)) v1 = ld_relaxed_v4(src + 4);
                        if ((all_nz(v0) && all_nz(v1)) || !live) break;
                        if (it > (1u << 22)) __trap();
                    }
                    *(uint4*)(hb + (ht >> 1) * 20 + (ht & 1) * 8) = v0;
                    *(uint4*)(hb + (ht >> 1) * 20 + (ht & 1) * 8 + 4) = v1;
                    if (live) {
                        __stcg((uint4*)src, make_uint4(0u, 0u, 0u, 0u));
                        __stcg((uint4*)(src + 4), make_uint4(0u, 0u, 0u, 0u));
                    }
                }
                if (ht == 0 && live) DBG(15);
                bar_sync(BAR_HELP, NHT);
                if (hw < 8) {
                    const float* hp = hb + (lane >> 1) * 20 + hw * 2 + (lane & 1);
                    float a = 0.f;
#pragma unroll
                    for (int i = 0; i < 8; i++) a += hp[i * 16 * 20];
#pragma unroll
                    for (int o = 16; o > 1; o >>= 1) a += __shfl_xor_sync(0xffffffffu, a, o);
                    const float a1 = __shfl_down_sync(0xffffffffu, a, 1);
                    if (live && lane == 0) ((uint32_t*)out)[u * 8 + hw] = pack_bf16(a, a1);
                }
                bar_sync(BAR_HELP, NHT);
                if (ht == 0) DBG(19 + b * 4);
            }
        }
        if (ht == 0) { DBG(10); DBGT(30); }
    }
}

typedef CUresult (*EncodeTiledFn)(CUtensorMap*, CUtensorMapDataType, cuuint32_t, void*, const cuuint64_t*,
                                  const cuuint64_t*, const cuuint32_t*, const cuuint32_t*, CUtensorMapInterleave,
                                  CUtensorMapSwizzle, CUtensorMapL2promotion, CUtensorMapFloatOOBfill);

}

extern "C" void kernel_launch(void* const* d_in, const int* in_sizes, int n_in, void* d_out, int out_size) {
    (void)in_sizes; (void)n_in; (void)out_size;
    const __nv_bfloat16* x = (const __nv_bfloat16*)d_in[0];
    void* kc = d_in[1];
    void* vc = d_in[2];
    const __nv_bfloat16* wq = (const __nv_bfloat16*)d_in[3];
    const __nv_bfloat16* wo = (const __nv_bfloat16*)d_in[4];

    static EncodeTiledFn enc = nullptr;
    static int num_sms = 0;
    if (!enc) {
        cudaDriverEntryPointQueryResult qr;
        cudaGetDriverEntryPoint("cuTensorMapEncodeTiled", (void**)&enc, cudaEnableDefault, &qr);
        int dev = 0;
        cudaGetDevice(&dev);
        cudaDeviceGetAttribute(&num_sms, cudaDevAttrMultiProcessorCount, dev);
        cudaFuncSetAttribute(gqa_decode_kernel, cudaFuncAttributeMaxDynamicSharedMemorySize, SMEM_BYTES);
    }
    CUtensorMap mk, mv;
    cuuint64_t gd[3] = {64, (cuuint64_t)NG * SK, 2};
    cuuint64_t gs[2] = {256, 128};
    cuuint32_t box[3] = {64, TILE, 2};
    cuuint32_t es[3] = {1, 1, 1};
    enc(&mk, CU_TENSOR_MAP_DATA_TYPE_BFLOAT16, 3, kc, gd, gs, box, es, CU_TENSOR_MAP_INTERLEAVE_NONE,
        CU_TENSOR_MAP_SWIZZLE_128B, CU_TENSOR_MAP_L2_PROMOTION_L2_256B, CU_TENSOR_MAP_FLOAT_OOB_FILL_NONE);
    enc(&mv, CU_TENSOR_MAP_DATA_TYPE_BFLOAT16, 3, vc, gd, gs, box, es, CU_TENSOR_MAP_INTERLEAVE_NONE,
        CU_TENSOR_MAP_SWIZZLE_128B, CU_TENSOR_MAP_L2_PROMOTION_L2_256B, CU_TENSOR_MAP_FLOAT_OOB_FILL_NONE);
    int grid = num_sms < MAX_CTAS ? num_sms : MAX_CTAS;
    gqa_decode_kernel<<<grid, NTHREADS, SMEM_BYTES>>>(mk, mv, x, wq, wo, (__nv_bfloat16*)d_out);
}
```

```cpp
#include <cuda_runtime.h>
#include <cuda.h>
#include <cuda_bf16.h>
#include <stdint.h>

namespace {

constexpr int BATCH = 2, DM = 576, HQ = 32, HKV = 16, SK = 32768, DH = 128;
constexpr int NG = BATCH * HKV;
constexpr int QN = HQ * DH;
#define TILE_KEYS 32
#define NSTAGES 6
#define NINFLIGHT 4
constexpr int TILE = TILE_KEYS;
constexpr int NCW = TILE / 16;
constexpr int STAGES = NSTAGES;
constexpr int INFLIGHT = NINFLIGHT;
constexpr int TILE_BYTES = TILE * DH * 2;
constexpr int STAGE_BYTES = 2 * TILE_BYTES;
constexpr int TILES_PER_G = SK / TILE;
constexpr int NTILES = NG * TILES_PER_G;
constexpr int NHW = 9;
constexpr int NHT = NHW * 32;
constexpr int NCT = NCW * 32;
constexpr int NTHREADS = NCT + 32 + NHT;
constexpr int NSLICE = 128;
constexpr int MAX_CTAS = 160;
constexpr int REC_W = 36;
constexpr int NUNIT = BATCH * DM / 16;
constexpr int WO_PITCH = DM * 2 + 16;

constexpr int SM_RING = 0;
constexpr int WO_BYTES = 32 * WO_PITCH;
constexpr int SM_WO = SM_RING + STAGES * STAGE_BYTES;
constexpr int SM_Q = SM_WO + WO_BYTES;
constexpr int SM_PART = SM_Q + BATCH * QN * 2;
constexpr int SM_ML = SM_PART + 2 * NCW * 2 * DH * 4;
constexpr int SM_HB = SM_ML + 2 * NCW * 4 * 4;
constexpr int SM_HM = SM_HB + NSLICE * 20 * 4;
constexpr int SM_HR = SM_HM + 2 * MAX_CTAS * 4;
constexpr int SM_HO = SM_HR + NHW * 64 * 4;
constexpr int SM_HY = SM_HO + NHW * 64 * 4;
constexpr int SM_BAR = SM_HY + NHW * 128 * 4;
constexpr int SM_TID = SM_BAR + (2 * STAGES + 3 + NG) * 8;
constexpr int SM_TOTAL = SM_TID + STAGES * 4;
constexpr int SMEM_BYTES = SM_TOTAL;
static_assert(SMEM_BYTES <= 232448, "too much shared memory");
static_assert(INFLIGHT >= 2 && INFLIGHT < STAGES, "inflight");

__device__ unsigned int g_tile_counter;
__device__ __align__(16) uint32_t g_q[BATCH * QN / 2];
__device__ __align__(16) float g_rec[NG * 2 * 4 * MAX_CTAS * REC_W];
__device__ __align__(16) float g_pout[BATCH * NSLICE * DM];

__device__ __forceinline__ uint32_t smem_u32(const void* p) { return (uint32_t)__cvta_generic_to_shared(p); }
__device__ __forceinline__ void mbar_init(uint32_t bar, uint32_t cnt) {
    asm volatile("mbarrier.init.shared::cta.b64 [%0], %1;" ::"r"(bar), "r"(cnt));
}
__device__ __forceinline__ void mbar_expect_tx(uint32_t bar, uint32_t bytes) {
    asm volatile("mbarrier.arrive.expect_tx.shared::cta.b64 _, [%0], %1;" ::"r"(bar), "r"(bytes) : "memory");
}
__device__ __forceinline__ void mbar_arrive(uint32_t bar) {
    asm volatile("mbarrier.arrive.shared::cta.b64 _, [%0];" ::"r"(bar) : "memory");
}
__device__ __forceinline__ void mbar_wait(uint32_t bar, uint32_t parity) {
    uint32_t done;
    for (uint32_t it = 0;; it++) {
        asm volatile(
            "{\n.reg .pred p;\n"
            "mbarrier.try_wait.parity.shared::cta.b64 p, [%1], %2;\n"
            "selp.u32 %0, 1, 0, p;\n}\n"
            : "=r"(done)
            : "r"(bar), "r"(parity)
            : "memory");
        if (done) break;
        if (it > (1u << 26)) __trap();
    }
}
__device__ __forceinline__ void tma_load_3d(uint32_t dst, const CUtensorMap* m, int row, uint32_t bar, uint64_t pol) {
    asm volatile(
        "cp.async.bulk.tensor.3d.shared::cluster.global.mbarrier::complete_tx::bytes.L2::cache_hint "
        "[%0], [%1, {%3, %4, %5}], [%2], %6;" ::"r"(dst),
        "l"((uint64_t)m), "r"(bar), "r"(0), "r"(row), "r"(0), "l"(pol)
        : "memory");
}
__device__ __forceinline__ void bulk_load(uint32_t dst, const void* src, uint32_t bytes, uint32_t bar) {
    asm volatile("cp.async.bulk.shared::cluster.global.mbarrier::complete_tx::bytes [%0], [%1], %2, [%3];" ::"r"(dst),
                 "l"(src), "r"(bytes), "r"(bar)
                 : "memory");
}
__device__ __forceinline__ void ldsm_x4(uint32_t (&r)[4], uint32_t addr) {
    asm volatile("ldmatrix.sync.aligned.m8n8.x4.shared.b16 {%0,%1,%2,%3}, [%4];"
                 : "=r"(r[0]), "=r"(r[1]), "=r"(r[2]), "=r"(r[3])
                 : "r"(addr)
                 : "memory");
}
__device__ __forceinline__ void ldsm_x4_t(uint32_t (&r)[4], uint32_t addr) {
    asm volatile("ldmatrix.sync.aligned.m8n8.x4.trans.shared.b16 {%0,%1,%2,%3}, [%4];"
                 : "=r"(r[0]), "=r"(r[1]), "=r"(r[2]), "=r"(r[3])
                 : "r"(addr)
                 : "memory");
}
__device__ __forceinline__ void mma_bf16(float (&c)[4], uint32_t a0, uint32_t a1, uint32_t a2, uint32_t a3, uint32_t b0,
                                         uint32_t b1) {
    asm volatile(
        "mma.sync.aligned.m16n8k16.row.col.f32.bf16.bf16.f32 {%0,%1,%2,%3}, {%4,%5,%6,%7}, {%8,%9}, {%0,%1,%2,%3};"
        : "+f"(c[0]), "+f"(c[1]), "+f"(c[2]), "+f"(c[3])
        : "r"(a0), "r"(a1), "r"(a2), "r"(a3), "r"(b0), "r"(b1));
}
__device__ __forceinline__ float ex2(float x) {
    float y;
    asm("ex2.approx.ftz.f32 %0, %1;" : "=f"(y) : "f"(x));
    return y;
}
__device__ __forceinline__ uint32_t pack_bf16(float lo, float hi) {
    uint32_t r;
    asm("cvt.rn.bf16x2.f32 %0, %1, %2;" : "=r"(r) : "f"(hi), "f"(lo));
    return r;
}
__device__ __forceinline__ void bar_sync(int id, int n) { asm volatile("bar.sync %0, %1;" ::"r"(id), "r"(n) : "memory"); }
__device__ __forceinline__ float nz(float v) { return (__float_as_uint(v) == 0u) ? __uint_as_float(0x80000000u) : v; }
__device__ __forceinline__ uint4 ld_relaxed_v4(const void* p) {
    uint4 v;
    asm volatile("ld.relaxed.gpu.global.v4.u32 {%0,%1,%2,%3}, [%4];"
                 : "=r"(v.x), "=r"(v.y), "=r"(v.z), "=r"(v.w)
                 : "l"(p)
                 : "memory");
    return v;
}
__device__ __forceinline__ bool all_nz(const uint4& v) { return v.x != 0u && v.y != 0u && v.z != 0u && v.w != 0u; }
__device__ __forceinline__ uint4 poll_v4(const void* p, uint4 v) {
    uint32_t it = 0;
    while (!all_nz(v)) {
        v = ld_relaxed_v4(p);
        if (++it > (1u << 22)) __trap();
    }
    return v;
}
__device__ __forceinline__ float bf_lo(uint32_t u) { return __uint_as_float(u << 16); }
__device__ __forceinline__ float bf_hi(uint32_t u) { return __uint_as_float(u & 0xffff0000u); }

enum { BAR_CONS = 1, BAR_HELP = 2 };

__global__ void __launch_bounds__(NTHREADS, 1)
gqa_decode_kernel(const __grid_constant__ CUtensorMap map_k, const __grid_constant__ CUtensorMap map_v,
                  const __nv_bfloat16* __restrict__ x, const __nv_bfloat16* __restrict__ wq,
                  const __nv_bfloat16* __restrict__ wo, __nv_bfloat16* __restrict__ out) {
    extern __shared__ __align__(1024) uint8_t smem[];
    const uint32_t sbase = smem_u32(smem);
    if (sbase & 1023u) __trap();
    const int tid = threadIdx.x, warp = tid >> 5, lane = tid & 31;
    const int nc = gridDim.x, cta = blockIdx.x;
    const uint32_t bar_full = sbase + SM_BAR, bar_empty = bar_full + STAGES * 8, bar_sig = bar_full + 2 * STAGES * 8;
    const uint32_t bar_q = bar_sig + 3 * 8;
    volatile int* tile_id = (volatile int*)(smem + SM_TID);

    constexpr int NSTATIC = 2;
    uint64_t pol;
    asm volatile("createpolicy.fractional.L2::evict_first.b64 %0, 1.0;" : "=l"(pol));
    const int ht = tid - (NCT + 32), hw = ht >> 5;
    const int r0 = hw * 8 + (lane >> 2);
    uint4 w[8];
    uint32_t xv0 = 0u, xv1 = 0u;
    unsigned a0 = 0u;
    if (ht >= 0) {
        if (cta < NSLICE) {
            const uint4* wp = (const uint4*)(wq + (size_t)r0 * QN + cta * 32 + (lane & 3) * 8);
#pragma unroll
            for (int i = 0; i < 8; i++) w[i] = __ldg(wp + (size_t)i * 72 * QN / 8);
        }
        xv0 = ((const uint32_t*)x)[ht];
        xv1 = ((const uint32_t*)x)[NHT + ht];
    } else if (tid == NCT) {
        a0 = atomicAdd(&g_tile_counter, 2u);
        for (int s = 0; s < STAGES; s++) {
            mbar_init(bar_full + s * 8, 1);
            mbar_init(bar_empty + s * 8, NCW);
        }
        mbar_init(bar_sig, NCW);
        mbar_init(bar_sig + 8, NCW);
        mbar_init(bar_sig + 16, 1);
        for (int g = 0; g < NG; g++) mbar_init(bar_q + g * 8, 1);
        asm volatile("fence.mbarrier_init.release.cluster;" ::: "memory");
        asm volatile("fence.proxy.async.shared::cta;" ::: "memory");
    }
    __syncthreads();
    if (tid == NCT) {
#pragma unroll
        for (int s = 0; s < NSTATIC; s++) {
            const int t = cta + s * nc;
            tile_id[s] = t;
            mbar_expect_tx(bar_full + s * 8, STAGE_BYTES);
            tma_load_3d(sbase + SM_RING + s * STAGE_BYTES, &map_k, t * TILE, bar_full + s * 8, pol);
            tma_load_3d(sbase + SM_RING + s * STAGE_BYTES + TILE_BYTES, &map_v, t * TILE, bar_full + s * 8, pol);
        }
    }

    if (warp == NCW) {
        if (lane == 0) {
            unsigned a1;
            const int dyn_base = NSTATIC * nc;
            a1 = a0 + 1;
            int t = dyn_base + (int)a0, tn = dyn_base + (int)a1;
            int s = NSTATIC % STAGES, s2 = 0;
            uint32_t ph = (NSTATIC == STAGES) ? 0 : 1, ph2 = 0;
            int pending = NSTATIC;
            while (t < NTILES) {
                int tnn = dyn_base + (int)atomicAdd(&g_tile_counter, 1u);
                if (pending >= INFLIGHT) {
                    mbar_wait(bar_full + s2 * 8, ph2);
                    if (++s2 == STAGES) { s2 = 0; ph2 ^= 1; }
                    pending--;
                }
                pending++;
                mbar_wait(bar_empty + s * 8, ph);
                tile_id[s] = t;
                mbar_expect_tx(bar_full + s * 8, STAGE_BYTES);
                tma_load_3d(sbase + SM_RING + s * STAGE_BYTES, &map_k, t * TILE, bar_full + s * 8, pol);
                tma_load_3d(sbase + SM_RING + s * STAGE_BYTES + TILE_BYTES, &map_v, t * TILE, bar_full + s * 8, pol);
                if (++s == STAGES) { s = 0; ph ^= 1; }
                t = tn;
                tn = tnn;
            }
            mbar_wait(bar_empty + s * 8, ph);
            tile_id[s] = -1;
            mbar_arrive(bar_full + s * 8);
#pragma unroll 1
            for (; pending > 0; pending--) {
                mbar_wait(bar_full + s2 * 8, ph2);
                if (++s2 == STAGES) { s2 = 0; ph2 ^= 1; }
            }
            if (cta < NSLICE) {
                mbar_expect_tx(bar_sig + 16, 32 * DM * 2);
                for (int r = 0; r < 32; r++)
                    bulk_load(sbase + SM_WO + r * WO_PITCH, wo + (size_t)(cta * 32 + r) * DM, DM * 2, bar_sig + 16);
            }
        }
    } else if (warp < NCW) {
        const int g8 = lane >> 2, t4 = lane & 3;
        const float SCALE = 0.08838834764831845f * 1.4426950408889634f;
        float acc[8][4];
        uint32_t qf[8][2];
        float m_run = -INFINITY, l_run = 0.f;
        int cur_g = -1, next_g = 0, fl = 0;
        bool sig0 = false;
        const int krow = warp * 16 + (lane & 7);
        const int kch = lane >> 3;
        const int vrow = warp * 16 + ((lane >> 4) << 3) + (lane & 7);
        const int vch = (lane >> 3) & 1;
        float* spart = (float*)(smem + SM_PART);
        float* sml = (float*)(smem + SM_ML);

        int s = 0;
        uint32_t ph = 0;
        while (true) {
            mbar_wait(bar_full + s * 8, ph);
            const int t = tile_id[s];
            const int g = (t < 0) ? NG : (t / TILES_PER_G);
            if (g != cur_g) {
                if (cur_g >= 0) {
                    float* pp = spart + (fl * NCW + warp) * 2 * DH;
                    float* pm = sml + (fl * NCW + warp) * 4;
                    float l = l_run;
                    l += __shfl_xor_sync(0xffffffffu, l, 1);
                    l += __shfl_xor_sync(0xffffffffu, l, 2);
                    if (t4 == 0) {
#pragma unroll
                        for (int mt = 0; mt < 8; mt++) {
                            *(float2*)(pp + (mt * 16 + g8) * 2) = make_float2(acc[mt][0], acc[mt][1]);
                            *(float2*)(pp + (mt * 16 + g8 + 8) * 2) = make_float2(acc[mt][2], acc[mt][3]);
                        }
                        if (g8 < 2) *(float2*)(pm + g8 * 2) = make_float2(m_run, l);
                    }
                    bar_sync(BAR_CONS, NCT);
                    const float* bp = spart + fl * NCW * 2 * DH;
                    const float* bm = sml + fl * NCW * 4;
                    float4 ml[NCW];
#pragma unroll
                    for (int wv = 0; wv < NCW; wv++) ml[wv] = *(const float4*)(bm + wv * 4);
                    float M0 = ml[0].x, M1 = ml[0].z;
#pragma unroll
                    for (int wv = 1; wv < NCW; wv++) { M0 = fmaxf(M0, ml[wv].x); M1 = fmaxf(M1, ml[wv].z); }
                    float L0 = 0.f, L1 = 0.f;
#pragma unroll
                    for (int wv = 0; wv < NCW; wv++) {
                        ml[wv].x = ex2(ml[wv].x - M0);
                        ml[wv].z = ex2(ml[wv].z - M1);
                        L0 = fmaf(ml[wv].x, ml[wv].y, L0);
                        L1 = fmaf(ml[wv].z, ml[wv].w, L1);
                    }
#pragma unroll
                    for (int d = tid; d < DH; d += NCT) {
                        float o0 = 0.f, o1 = 0.f;
#pragma unroll
                        for (int wv = 0; wv < NCW; wv++) {
                            const float2 f = *(const float2*)(bp + wv * 2 * DH + d * 2);
                            o0 = fmaf(ml[wv].x, f.x, o0);
                            o1 = fmaf(ml[wv].z, f.y, o1);
                        }
                        float* rp = g_rec + ((size_t)(cur_g * 8 + (d >> 5)) * MAX_CTAS + cta) * REC_W;
                        __stcg(rp + lane, nz(o0));
                        __stcg(rp + 4 * MAX_CTAS * REC_W + lane, nz(o1));
                        if (lane < 2) {
                            const float4 f = make_float4(nz(lane ? M1 : M0), nz(lane ? L1 : L0), 1.f, 1.f);
                            __stcg((float4*)(rp + lane * 4 * MAX_CTAS * REC_W + 32), f);
                        }
                    }
                    fl ^= 1;
                    next_g = cur_g + 1;
                }
                for (; next_g < g; next_g++) {
                    mbar_wait(bar_q + next_g * 8, 0);
                    for (int idx = tid; idx < 2 * DH; idx += NCT) {
                        float* rp = g_rec + ((size_t)(next_g * 8 + (idx >> 5)) * MAX_CTAS + cta) * REC_W;
                        __stcg(rp + lane, -0.0f);
                        if (lane < 4) __stcg(rp + 32 + lane, lane == 0 ? -INFINITY : (lane == 1 ? -0.0f : 1.0f));
                    }
                }
                if (!sig0 && g >= HKV) { if (lane == 0) mbar_arrive(bar_sig); sig0 = true; }
                if (t < 0) break;
                cur_g = g;
                mbar_wait(bar_q + g * 8, 0);
                const uint32_t* sq32 =
                    (const uint32_t*)(smem + SM_Q) + ((g >> 4) * QN + ((g & 15) * 2 + (g8 & 1)) * DH) / 2;
#pragma unroll
                for (int ks = 0; ks < 8; ks++) {
                    const uint32_t v0 = sq32[ks * 8 + t4], v1 = sq32[ks * 8 + 4 + t4];
                    qf[ks][0] = (g8 < 2) ? v0 : 0u;
                    qf[ks][1] = (g8 < 2) ? v1 : 0u;
                }
#pragma unroll
                for (int mt = 0; mt < 8; mt++) acc[mt][0] = acc[mt][1] = acc[mt][2] = acc[mt][3] = 0.f;
                m_run = -INFINITY;
                l_run = 0.f;
            }
            const uint32_t kb = sbase + SM_RING + s * STAGE_BYTES, vb = kb + TILE_BYTES;
            uint32_t kf[2][4][4], vf[8][4];
#pragma unroll
            for (int nt = 0; nt < 2; nt++)
#pragma unroll
                for (int j = 0; j < 4; j++) {
                    const int row = krow + nt * 8;
                    const int ch = (j & 1) * 4 + kch;
                    ldsm_x4(kf[nt][j], kb + (j >> 1) * (TILE * 128) + row * 128 + ((ch ^ (row & 7)) << 4));
                }
#pragma unroll
            for (int mt = 0; mt < 8; mt++) {
                const int ch = (mt & 3) * 2 + vch;
                ldsm_x4_t(vf[mt], vb + (mt >> 2) * (TILE * 128) + vrow * 128 + ((ch ^ (vrow & 7)) << 4));
            }
            __syncwarp();
            if (lane == 0) mbar_arrive(bar_empty + s * 8);
            if (++s == STAGES) { s = 0; ph ^= 1; }

            float sc[2][2][4];
#pragma unroll
            for (int nt = 0; nt < 2; nt++)
#pragma unroll
                for (int hh = 0; hh < 2; hh++) {
                    sc[nt][hh][0] = sc[nt][hh][1] = sc[nt][hh][2] = sc[nt][hh][3] = 0.f;
#pragma unroll
                    for (int jj = 0; jj < 2; jj++) {
                        const int j = hh * 2 + jj;
                        mma_bf16(sc[nt][hh], qf[2 * j][0], 0u, qf[2 * j][1], 0u, kf[nt][j][0], kf[nt][j][1]);
                        mma_bf16(sc[nt][hh], qf[2 * j + 1][0], 0u, qf[2 * j + 1][1], 0u, kf[nt][j][2], kf[nt][j][3]);
                    }
                }
            const float s0 = (sc[0][0][0] + sc[0][1][0]) * SCALE, s1 = (sc[0][0][1] + sc[0][1][1]) * SCALE;
            const float s2 = (sc[1][0][0] + sc[1][1][0]) * SCALE, s3 = (sc[1][0][1] + sc[1][1][1]) * SCALE;
            float mx = fmaxf(fmaxf(s0, s1), fmaxf(s2, s3));
            mx = fmaxf(mx, __shfl_xor_sync(0xffffffffu, mx, 1));
            mx = fmaxf(mx, __shfl_xor_sync(0xffffffffu, mx, 2));
            const float m_new = fmaxf(m_run, mx);
            const float alpha = ex2(m_run - m_new);
            m_run = m_new;
            const float p0 = ex2(s0 - m_new), p1 = ex2(s1 - m_new), p2 = ex2(s2 - m_new), p3 = ex2(s3 - m_new);
            l_run = fmaf(l_run, alpha, (p0 + p1) + (p2 + p3));
            const uint32_t pb0 = pack_bf16(p0, p1), pb1 = pack_bf16(p2, p3);
            const float al0 = __shfl_sync(0xffffffffu, alpha, 0), al1 = __shfl_sync(0xffffffffu, alpha, 4);
            if (al0 != 1.f || al1 != 1.f) {
#pragma unroll
                for (int mt = 0; mt < 8; mt++) {
                    acc[mt][0] *= al0;
                    acc[mt][1] *= al1;
                    acc[mt][2] *= al0;
                    acc[mt][3] *= al1;
                }
            }
#pragma unroll
            for (int mt = 0; mt < 8; mt++) mma_bf16(acc[mt], vf[mt][0], vf[mt][1], vf[mt][2], vf[mt][3], pb0, pb1);
        }
        if (lane == 0) mbar_arrive(bar_sig + 8);
    } else {
        float* hb = (float*)(smem + SM_HB);
        float* hm = (float*)(smem + SM_HM);
        float* hr = (float*)(smem + SM_HR);
        {
            int slice = cta;
            *(float2*)(hb + 2 * ht) = make_float2(bf_lo(xv0), bf_hi(xv0));
            *(float2*)(hb + DM + 2 * ht) = make_float2(bf_lo(xv1), bf_hi(xv1));
            bar_sync(BAR_HELP, NHT);
            for (; slice < NSLICE;) {
                float a0[8], a1[8];
#pragma unroll
                for (int j = 0; j < 8; j++) a0[j] = a1[j] = 0.f;
#pragma unroll
                for (int i = 0; i < 8; i++) {
                    const float x0 = hb[r0 + 72 * i], x1 = hb[DM + r0 + 72 * i];
                    const uint32_t u[4] = {w[i].x, w[i].y, w[i].z, w[i].w};
#pragma unroll
                    for (int j = 0; j < 4; j++) {
                        const float lo = bf_lo(u[j]), hi = bf_hi(u[j]);
                        a0[2 * j] = fmaf(x0, lo, a0[2 * j]);
                        a0[2 * j + 1] = fmaf(x0, hi, a0[2 * j + 1]);
                        a1[2 * j] = fmaf(x1, lo, a1[2 * j]);
                        a1[2 * j + 1] = fmaf(x1, hi, a1[2 * j + 1]);
                    }
                }
#pragma unroll
                for (int j = 0; j < 8; j++) {
#pragma unroll
                    for (int o = 4; o < 32; o <<= 1) {
                        a0[j] += __shfl_xor_sync(0xffffffffu, a0[j], o);
                        a1[j] += __shfl_xor_sync(0xffffffffu, a1[j], o);
                    }
                }
                if (lane < 4) {
#pragma unroll
                    for (int j = 0; j < 8; j++) {
                        hr[hw * 64 + lane * 8 + j] = a0[j];
                        hr[hw * 64 + 32 + lane * 8 + j] = a1[j];
                    }
                }
                bar_sync(BAR_HELP, NHT);
                if (ht < 32) {
                    float s0 = 0.f, s1 = 0.f;
#pragma unroll
                    for (int wv = 0; wv < NHW; wv++) {
                        const float2 f = *(const float2*)(hr + wv * 64 + ht * 2);
                        s0 += f.x;
                        s1 += f.y;
                    }
                    uint32_t u = pack_bf16(s0, s1);
                    if (u == 0u) u = 0x80000000u;
                    __stcg(g_q + ((ht >> 4) * QN + slice * 32) / 2 + (ht & 15), u);
                }
                slice += nc;
                if (slice < NSLICE) {
                    bar_sync(BAR_HELP, NHT);
                    const uint4* wp = (const uint4*)(wq + (size_t)r0 * QN + slice * 32 + (lane & 3) * 8);
#pragma unroll
                    for (int i = 0; i < 8; i++) w[i] = __ldg(wp + (size_t)i * 72 * QN / 8);
                }
            }
        }
        for (int g = hw; g < NG; g += NHW) {
            const uint4* src = (const uint4*)g_q + g * 32 + lane;
            uint4 v = ld_relaxed_v4(src);
            v = poll_v4(src, v);
            ((uint4*)(smem + SM_Q))[g * 32 + lane] = v;
            __syncwarp();
            if (lane == 0) mbar_arrive(bar_q + g * 8);
        }
        const int rr = ht / 9, part = ht - rr * 9;
        constexpr int MAXS = (NSLICE + 63) / 64;
        float o_b0[MAXS];
#pragma unroll 1
        for (int b = 0; b < BATCH; b++) {
            const bool live = (b == BATCH - 1);
            if (lane == 0) mbar_wait(bar_sig + b * 8, 0);
            __syncwarp();
            int si = 0;
#pragma unroll 1
            for (int slice = cta; slice < NSLICE; slice += nc, si++) {
                float* src = g_rec + (size_t)(b * HKV * 8 + slice) * MAX_CTAS * REC_W + ht * 4;
                constexpr int NR = MAX_CTAS / 32;
                uint4 v[NR];
#pragma unroll
                for (int k = 0; k < NR; k++) v[k] = (rr + 32 * k < nc) ? make_uint4(0u, 0u, 0u, 0u) : make_uint4(1u, 1u, 1u, 1u);
                for (uint32_t it = 0;; it++) {
#pragma unroll
                    for (int k = 0; k < NR; k++)
                        if (!all_nz(v[k])) v[k] = ld_relaxed_v4(src + k * NHT * 4);
                    bool ok = true;
#pragma unroll
                    for (int k = 0; k < NR; k++) ok = ok && all_nz(v[k]);
                    if (ok) break;
                    if (it > (1u << 22)) __trap();
                }
                if (part == 8) {
#pragma unroll
                    for (int k = 0; k < NR; k++)
                        if (rr + 32 * k < nc) {
                            hm[rr + 32 * k] = __uint_as_float(v[k].x);
                            hm[MAX_CTAS + rr + 32 * k] = __uint_as_float(v[k].y);
                        }
                }
                bar_sync(BAR_HELP, NHT);
                float M = -INFINITY;
#pragma unroll
                for (int k = 0; k < NR; k++)
                    if (lane + 32 * k < nc) M = fmaxf(M, hm[lane + 32 * k]);
#pragma unroll
                for (int o = 16; o > 0; o >>= 1) M = fmaxf(M, __shfl_xor_sync(0xffffffffu, M, o));
                float4 a = make_float4(0.f, 0.f, 0.f, 0.f);
#pragma unroll
                for (int k = 0; k < NR; k++)
                    if (rr + 32 * k < nc) {
                        const float e = ex2(hm[rr + 32 * k] - M);
                        a.x = fmaf(e, __uint_as_float(v[k].x), a.x);
                        a.y = fmaf(e, __uint_as_float(v[k].y), a.y);
                        a.z = fmaf(e, __uint_as_float(v[k].z), a.z);
                        a.w = fmaf(e, __uint_as_float(v[k].w), a.w);
                    }
                *(float4*)(hb + ht * 4) = a;
                bar_sync(BAR_HELP, NHT);
                float o0 = 0.f, o1 = 0.f, L = hb[lane * REC_W + 33];
#pragma unroll
                for (int r = 0; r < 32; r += 2) {
                    o0 += hb[r * REC_W + lane];
                    o1 += hb[(r + 1) * REC_W + lane];
                }
#pragma unroll
                for (int o = 16; o > 0; o >>= 1) L += __shfl_xor_sync(0xffffffffu, L, o);
                const float ob = __bfloat162float(__float2bfloat16((o0 + o1) / L));
                float oa = ob;
#pragma unroll
                for (int i = 0; i < MAXS; i++)
                    if (i == si) {
                        if (!live) o_b0[i] = ob;
                        oa = o_b0[i];
                    }
                __nv_bfloat16* ho = (__nv_bfloat16*)(smem + SM_HO) + hw * 64;
                ho[lane] = __float2bfloat16(oa);
                ho[32 + lane] = __float2bfloat16(ob);
                if (si > 0) {
                    bar_sync(BAR_HELP, NHT);
                    const uint32_t* gw = (const uint32_t*)(wo + (size_t)slice * 32 * DM) + ht;
                    for (int r = 0; r < 32; r++) *(uint32_t*)(smem + SM_WO + r * WO_PITCH + ht * 4) = __ldg(gw + r * (DM / 2));
                    bar_sync(BAR_HELP, NHT);
                } else if (live) {
                    mbar_wait(bar_sig + 16, 0);
                }
                __syncwarp();
                {
                    const int g8 = lane >> 2, t4 = lane & 3;
                    const uint32_t* ho32 = (const uint32_t*)ho + (g8 & 1) * 16 + t4;
                    uint32_t bf[4];
#pragma unroll
                    for (int i = 0; i < 4; i++) bf[i] = (g8 < 2) ? ho32[i * 4] : 0u;
                    const uint32_t wa = sbase + SM_WO + (((lane >> 4) << 3) + (lane & 7)) * WO_PITCH +
                                        (hw * 64 + ((lane >> 3) & 1) * 8) * 2;
                    uint32_t af[4][2][4];
#pragma unroll
                    for (int mt = 0; mt < 4; mt++) {
                        ldsm_x4_t(af[mt][0], wa + mt * 32);
                        ldsm_x4_t(af[mt][1], wa + mt * 32 + 16 * WO_PITCH);
                    }
                    float c[4][4];
#pragma unroll
                    for (int mt = 0; mt < 4; mt++) {
                        c[mt][0] = c[mt][1] = c[mt][2] = c[mt][3] = 0.f;
                        mma_bf16(c[mt], af[mt][0][0], af[mt][0][1], af[mt][0][2], af[mt][0][3], bf[0], bf[1]);
                    }
#pragma unroll
                    for (int mt = 0; mt < 4; mt++)
                        mma_bf16(c[mt], af[mt][1][0], af[mt][1][1], af[mt][1][2], af[mt][1][3], bf[2], bf[3]);
                    float* hy = (float*)(smem + SM_HY) + hw * 128;
                    if (t4 == 0) {
#pragma unroll
                        for (int mt = 0; mt < 4; mt++) {
                            hy[mt * 16 + g8] = c[mt][0];
                            hy[mt * 16 + g8 + 8] = c[mt][2];
                            hy[64 + mt * 16 + g8] = c[mt][1];
                            hy[64 + mt * 16 + g8 + 8] = c[mt][3];
                        }
                    }
                    __syncwarp();
                    const float4 y = *(const float4*)(hy + lane * 4);
                    if (live)
                        __stcg((float4*)(g_pout + (size_t)((lane >> 4) * NSLICE + slice) * DM + hw * 64 + (lane & 15) * 4),
                               make_float4(nz(y.x), nz(y.y), nz(y.z), nz(y.w)));
                }
#pragma unroll
                for (int k = 0; k < NR; k++)
                    if (rr + 32 * k < nc) __stcg((uint4*)(src + k * NHT * 4), make_uint4(0u, 0u, 0u, 0u));
                if (live) {
                    if (ht < 32) __stcg(g_q + ((ht >> 4) * QN + slice * 32) / 2 + (ht & 15), 0u);
                    if (slice == NSLICE - 1 && ht == 0) g_tile_counter = 0u;
                }
                bar_sync(BAR_HELP, NHT);
            }
#pragma unroll 1
            for (int u = cta; u < NUNIT; u += nc) {
                const int ub = u / (NUNIT / 2), uc = u - ub * (NUNIT / 2);
                float* src = g_pout + (size_t)(ub * NSLICE + (ht >> 1)) * DM + uc * 16 + (ht & 1) * 8;
                if (ht < 2 * NSLICE) {
                    uint4 v0 = make_uint4(0u, 0u, 0u, 0u), v1 = v0;
                    for (uint32_t it = 0;; it++) {
                        if (!all_nz(v0)) v0 = ld_relaxed_v4(src);
                        if (!all_nz(v1)) v1 = ld_relaxed_v4(src + 4);
                        if ((all_nz(v0) && all_nz(v1)) || !live) break;
                        if (it > (1u << 22)) __trap();
                    }
                    *(uint4*)(hb + (ht >> 1) * 20 + (ht & 1) * 8) = v0;
                    *(uint4*)(hb + (ht >> 1) * 20 + (ht & 1) * 8 + 4) = v1;
                }
                bar_sync(BAR_HELP, NHT);
                if (hw < 8) {
                    const float* hp = hb + (lane >> 1) * 20 + hw * 2 + (lane & 1);
                    float a = 0.f;
#pragma unroll
                    for (int i = 0; i < 8; i++) a += hp[i * 16 * 20];
#pragma unroll
                    for (int o = 16; o > 1; o >>= 1) a += __shfl_xor_sync(0xffffffffu, a, o);
                    const float a1 = __shfl_down_sync(0xffffffffu, a, 1);
                    if (live && lane == 0) ((uint32_t*)out)[u * 8 + hw] = pack_bf16(a, a1);
                    if (live) {
                        __stcg((uint4*)src, make_uint4(0u, 0u, 0u, 0u));
                        __stcg((uint4*)(src + 4), make_uint4(0u, 0u, 0u, 0u));
                    }
                }
                bar_sync(BAR_HELP, NHT);
            }
        }
    }
}

typedef CUresult (*EncodeTiledFn)(CUtensorMap*, CUtensorMapDataType, cuuint32_t, void*, const cuuint64_t*,
                                  const cuuint64_t*, const cuuint32_t*, const cuuint32_t*, CUtensorMapInterleave,
                                  CUtensorMapSwizzle, CUtensorMapL2promotion, CUtensorMapFloatOOBfill);

}

extern "C" void kernel_launch(void* const* d_in, const int* in_sizes, int n_in, void* d_out, int out_size) {
    (void)in_sizes; (void)n_in; (void)out_size;
    const __nv_bfloat16* x = (const __nv_bfloat16*)d_in[0];
    void* kc = d_in[1];
    void* vc = d_in[2];
    const __nv_bfloat16* wq = (const __nv_bfloat16*)d_in[3];
    const __nv_bfloat16* wo = (const __nv_bfloat16*)d_in[4];

    static EncodeTiledFn enc = nullptr;
    static int num_sms = 0;
    if (!enc) {
        cudaDriverEntryPointQueryResult qr;
        cudaGetDriverEntryPoint("cuTensorMapEncodeTiled", (void**)&enc, cudaEnableDefault, &qr);
        int dev = 0;
        cudaGetDevice(&dev);
        cudaDeviceGetAttribute(&num_sms, cudaDevAttrMultiProcessorCount, dev);
        cudaFuncSetAttribute(gqa_decode_kernel, cudaFuncAttributeMaxDynamicSharedMemorySize, SMEM_BYTES);
    }
    CUtensorMap mk, mv;
    cuuint64_t gd[3] = {64, (cuuint64_t)NG * SK, 2};
    cuuint64_t gs[2] = {256, 128};
    cuuint32_t box[3] = {64, TILE, 2};
    cuuint32_t es[3] = {1, 1, 1};
    enc(&mk, CU_TENSOR_MAP_DATA_TYPE_BFLOAT16, 3, kc, gd, gs, box, es, CU_TENSOR_MAP_INTERLEAVE_NONE,
        CU_TENSOR_MAP_SWIZZLE_128B, CU_TENSOR_MAP_L2_PROMOTION_L2_256B, CU_TENSOR_MAP_FLOAT_OOB_FILL_NONE);
    enc(&mv, CU_TENSOR_MAP_DATA_TYPE_BFLOAT16, 3, vc, gd, gs, box, es, CU_TENSOR_MAP_INTERLEAVE_NONE,
        CU_TENSOR_MAP_SWIZZLE_128B, CU_TENSOR_MAP_L2_PROMOTION_L2_256B, CU_TENSOR_MAP_FLOAT_OOB_FILL_NONE);
    int grid = num_sms < MAX_CTAS ? num_sms : MAX_CTAS;
    gqa_decode_kernel<<<grid, NTHREADS, SMEM_BYTES>>>(mk, mv, x, wq, wo, (__nv_bfloat16*)d_out);
}
```

```cpp
#include <cuda_runtime.h>
#include <cuda.h>
#include <cuda_bf16.h>
#include <stdint.h>

namespace {

constexpr int BATCH = 2, DM = 576, HQ = 32, HKV = 16, SK = 32768, DH = 128;
constexpr int NG = BATCH * HKV;
constexpr int QN = HQ * DH;
#define TILE_KEYS 32
#define NSTAGES 6
#define NINFLIGHT 4
constexpr int TILE = TILE_KEYS;
constexpr int NCW = TILE / 16;
constexpr int STAGES = NSTAGES;
constexpr int INFLIGHT = NINFLIGHT;
constexpr int TILE_BYTES = TILE * DH * 2;
constexpr int STAGE_BYTES = 2 * TILE_BYTES;
constexpr int TILES_PER_G = SK / TILE;
constexpr int NTILES = NG * TILES_PER_G;
constexpr int NHW = 9;
constexpr int NHT = NHW * 32;
constexpr int NCT = NCW * 32;
constexpr int NTHREADS = NCT + 32 + NHT;
constexpr int NSLICE = 128;
constexpr int MAX_CTAS = 160;
constexpr int REC_W = 36;
constexpr int NUNIT = BATCH * DM / 16;
constexpr int WO_PITCH = DM * 2 + 16;

constexpr int SM_RING = 0;
constexpr int WO_BYTES = 32 * WO_PITCH;
constexpr int SM_WO = SM_RING + STAGES * STAGE_BYTES;
constexpr int SM_Q = SM_WO + WO_BYTES;
constexpr int SM_PART = SM_Q + BATCH * QN * 2;
constexpr int SM_ML = SM_PART + 2 * NCW * 2 * DH * 4;
constexpr int SM_HB = SM_ML + 2 * NCW * 4 * 4;
constexpr int SM_HM = SM_HB + NSLICE * 20 * 4;
constexpr int SM_HR = SM_HM + 2 * MAX_CTAS * 4;
constexpr int SM_HO = SM_HR + NHW * 64 * 4;
constexpr int SM_HY = SM_HO + NHW * 64 * 4;
constexpr int SM_BAR = SM_HY + NHW * 128 * 4;
constexpr int SM_TID = SM_BAR + (2 * STAGES + 4 + NG) * 8;
constexpr int SM_TOTAL = SM_TID + STAGES * 4;
constexpr int SMEM_BYTES = SM_TOTAL;
static_assert(SMEM_BYTES <= 232448, "too much shared memory");
static_assert(INFLIGHT >= 2 && INFLIGHT < STAGES, "inflight");

__device__ unsigned int g_tile_counter;
__device__ __align__(16) uint32_t g_q[BATCH * QN / 2];
__device__ __align__(16) float g_rec[NG * 2 * 4 * MAX_CTAS * REC_W];
__device__ __align__(16) float g_pout[BATCH * NSLICE * DM];

__device__ __forceinline__ uint32_t smem_u32(const void* p) { return (uint32_t)__cvta_generic_to_shared(p); }
__device__ __forceinline__ void mbar_init(uint32_t bar, uint32_t cnt) {
    asm volatile("mbarrier.init.shared::cta.b64 [%0], %1;" ::"r"(bar), "r"(cnt));
}
__device__ __forceinline__ void mbar_expect_tx(uint32_t bar, uint32_t bytes) {
    asm volatile("mbarrier.arrive.expect_tx.shared::cta.b64 _, [%0], %1;" ::"r"(bar), "r"(bytes) : "memory");
}
__device__ __forceinline__ void mbar_arrive(uint32_t bar) {
    asm volatile("mbarrier.arrive.shared::cta.b64 _, [%0];" ::"r"(bar) : "memory");
}
__device__ __forceinline__ void mbar_wait(uint32_t bar, uint32_t parity) {
    uint32_t done;
    for (uint32_t it = 0;; it++) {
        asm volatile(
            "{\n.reg .pred p;\n"
            "mbarrier.try_wait.parity.shared::cta.b64 p, [%1], %2;\n"
            "selp.u32 %0, 1, 0, p;\n}\n"
            : "=r"(done)
            : "r"(bar), "r"(parity)
            : "memory");
        if (done) break;
        if (it > (1u << 26)) __trap();
    }
}
__device__ __forceinline__ void tma_load_3d(uint32_t dst, const CUtensorMap* m, int row, uint32_t bar, uint64_t pol) {
    asm volatile(
        "cp.async.bulk.tensor.3d.shared::cluster.global.mbarrier::complete_tx::bytes.L2::cache_hint "
        "[%0], [%1, {%3, %4, %5}], [%2], %6;" ::"r"(dst),
        "l"((uint64_t)m), "r"(bar), "r"(0), "r"(row), "r"(0), "l"(pol)
        : "memory");
}
__device__ __forceinline__ void bulk_load(uint32_t dst, const void* src, uint32_t bytes, uint32_t bar) {
    asm volatile("cp.async.bulk.shared::cluster.global.mbarrier::complete_tx::bytes [%0], [%1], %2, [%3];" ::"r"(dst),
                 "l"(src), "r"(bytes), "r"(bar)
                 : "memory");
}
__device__ __forceinline__ void ldsm_x4(uint32_t (&r)[4], uint32_t addr) {
    asm volatile("ldmatrix.sync.aligned.m8n8.x4.shared.b16 {%0,%1,%2,%3}, [%4];"
                 : "=r"(r[0]), "=r"(r[1]), "=r"(r[2]), "=r"(r[3])
                 : "r"(addr)
                 : "memory");
}
__device__ __forceinline__ void ldsm_x4_t(uint32_t (&r)[4], uint32_t addr) {
    asm volatile("ldmatrix.sync.aligned.m8n8.x4.trans.shared.b16 {%0,%1,%2,%3}, [%4];"
                 : "=r"(r[0]), "=r"(r[1]), "=r"(r[2]), "=r"(r[3])
                 : "r"(addr)
                 : "memory");
}
__device__ __forceinline__ void mma_bf16(float (&c)[4], uint32_t a0, uint32_t a1, uint32_t a2, uint32_t a3, uint32_t b0,
                                         uint32_t b1) {
    asm volatile(
        "mma.sync.aligned.m16n8k16.row.col.f32.bf16.bf16.f32 {%0,%1,%2,%3}, {%4,%5,%6,%7}, {%8,%9}, {%0,%1,%2,%3};"
        : "+f"(c[0]), "+f"(c[1]), "+f"(c[2]), "+f"(c[3])
        : "r"(a0), "r"(a1), "r"(a2), "r"(a3), "r"(b0), "r"(b1));
}
__device__ __forceinline__ float ex2(float x) {
    float y;
    asm("ex2.approx.ftz.f32 %0, %1;" : "=f"(y) : "f"(x));
    return y;
}
__device__ __forceinline__ uint32_t pack_bf16(float lo, float hi) {
    uint32_t r;
    asm("cvt.rn.bf16x2.f32 %0, %1, %2;" : "=r"(r) : "f"(hi), "f"(lo));
    return r;
}
__device__ __forceinline__ void bar_sync(int id, int n) { asm volatile("bar.sync %0, %1;" ::"r"(id), "r"(n) : "memory"); }
__device__ __forceinline__ float nz(float v) { return (__float_as_uint(v) == 0u) ? __uint_as_float(0x80000000u) : v; }
__device__ __forceinline__ uint4 ld_relaxed_v4(const void* p) {
    uint4 v;
    asm volatile("ld.relaxed.gpu.global.v4.u32 {%0,%1,%2,%3}, [%4];"
                 : "=r"(v.x), "=r"(v.y), "=r"(v.z), "=r"(v.w)
                 : "l"(p)
                 : "memory");
    return v;
}
__device__ __forceinline__ bool all_nz(const uint4& v) { return v.x != 0u && v.y != 0u && v.z != 0u && v.w != 0u; }
__device__ __forceinline__ uint4 poll_v4(const void* p, uint4 v) {
    uint32_t it = 0;
    while (!all_nz(v)) {
        v = ld_relaxed_v4(p);
        if (++it > (1u << 22)) __trap();
    }
    return v;
}
__device__ __forceinline__ float bf_lo(uint32_t u) { return __uint_as_float(u << 16); }
__device__ __forceinline__ float bf_hi(uint32_t u) { return __uint_as_float(u & 0xffff0000u); }

enum { BAR_CONS = 1, BAR_HELP = 2 };

__global__ void __launch_bounds__(NTHREADS, 1)
gqa_decode_kernel(const __grid_constant__ CUtensorMap map_k, const __grid_constant__ CUtensorMap map_v,
                  const __nv_bfloat16* __restrict__ x, const __nv_bfloat16* __restrict__ wq,
                  const __nv_bfloat16* __restrict__ wo, __nv_bfloat16* __restrict__ out) {
    extern __shared__ __align__(1024) uint8_t smem[];
    const uint32_t sbase = smem_u32(smem);
    if (sbase & 1023u) __trap();
    const int tid = threadIdx.x, warp = tid >> 5, lane = tid & 31;
    const int nc = gridDim.x, cta = blockIdx.x;
    const uint32_t bar_full = sbase + SM_BAR, bar_empty = bar_full + STAGES * 8, bar_sig = bar_full + 2 * STAGES * 8;
    const uint32_t bar_zero = bar_sig + 3 * 8, bar_q = bar_sig + 4 * 8;
    volatile int* tile_id = (volatile int*)(smem + SM_TID);

    constexpr int NSTATIC = 2;
    uint64_t pol;
    asm volatile("createpolicy.fractional.L2::evict_first.b64 %0, 1.0;" : "=l"(pol));
    const int ht = tid - (NCT + 32), hw = ht >> 5;
    const int r0 = hw * 8 + (lane >> 2);
    uint4 w[8];
    uint32_t xv0 = 0u, xv1 = 0u;
    unsigned a0 = 0u;
    if (ht >= 0) {
        if (cta < NSLICE) {
            const uint4* wp = (const uint4*)(wq + (size_t)r0 * QN + cta * 32 + (lane & 3) * 8);
#pragma unroll
            for (int i = 0; i < 8; i++) w[i] = __ldg(wp + (size_t)i * 72 * QN / 8);
        }
        xv0 = ((const uint32_t*)x)[ht];
        xv1 = ((const uint32_t*)x)[NHT + ht];
    } else if (tid == NCT) {
        a0 = atomicAdd(&g_tile_counter, 2u);
        for (int s = 0; s < STAGES; s++) {
            mbar_init(bar_full + s * 8, 1);
            mbar_init(bar_empty + s * 8, NCW);
        }
        mbar_init(bar_sig, NCW);
        mbar_init(bar_sig + 8, NCW);
        mbar_init(bar_sig + 16, 1);
        mbar_init(bar_zero, NHW);
        for (int g = 0; g < NG; g++) mbar_init(bar_q + g * 8, 1);
        asm volatile("fence.mbarrier_init.release.cluster;" ::: "memory");
        asm volatile("fence.proxy.async.shared::cta;" ::: "memory");
    }
    __syncthreads();
    if (tid == NCT) {
#pragma unroll
        for (int s = 0; s < NSTATIC; s++) {
            const int t = cta + s * nc;
            tile_id[s] = t;
            mbar_expect_tx(bar_full + s * 8, STAGE_BYTES);
            tma_load_3d(sbase + SM_RING + s * STAGE_BYTES, &map_k, t * TILE, bar_full + s * 8, pol);
            tma_load_3d(sbase + SM_RING + s * STAGE_BYTES + TILE_BYTES, &map_v, t * TILE, bar_full + s * 8, pol);
        }
    }

    if (warp == NCW) {
        if (lane == 0) {
            unsigned a1;
            const int dyn_base = NSTATIC * nc;
            a1 = a0 + 1;
            int t = dyn_base + (int)a0, tn = dyn_base + (int)a1;
            int s = NSTATIC % STAGES, s2 = 0;
            uint32_t ph = (NSTATIC == STAGES) ? 0 : 1, ph2 = 0;
            int pending = NSTATIC;
            while (t < NTILES) {
                int tnn = dyn_base + (int)atomicAdd(&g_tile_counter, 1u);
                if (pending >= INFLIGHT) {
                    mbar_wait(bar_full + s2 * 8, ph2);
                    if (++s2 == STAGES) { s2 = 0; ph2 ^= 1; }
                    pending--;
                }
                pending++;
                mbar_wait(bar_empty + s * 8, ph);
                tile_id[s] = t;
                mbar_expect_tx(bar_full + s * 8, STAGE_BYTES);
                tma_load_3d(sbase + SM_RING + s * STAGE_BYTES, &map_k, t * TILE, bar_full + s * 8, pol);
                tma_load_3d(sbase + SM_RING + s * STAGE_BYTES + TILE_BYTES, &map_v, t * TILE, bar_full + s * 8, pol);
                if (++s == STAGES) { s = 0; ph ^= 1; }
                t = tn;
                tn = tnn;
            }
            mbar_wait(bar_empty + s * 8, ph);
            tile_id[s] = -1;
            mbar_arrive(bar_full + s * 8);
#pragma unroll 1
            for (; pending > 0; pending--) {
                mbar_wait(bar_full + s2 * 8, ph2);
                if (++s2 == STAGES) { s2 = 0; ph2 ^= 1; }
            }
            if (cta < NSLICE) {
                mbar_expect_tx(bar_sig + 16, 32 * DM * 2);
                for (int r = 0; r < 32; r++)
                    bulk_load(sbase + SM_WO + r * WO_PITCH, wo + (size_t)(cta * 32 + r) * DM, DM * 2, bar_sig + 16);
            }
        }
    } else if (warp < NCW) {
        const int g8 = lane >> 2, t4 = lane & 3;
        const float SCALE = 0.08838834764831845f * 1.4426950408889634f;
        float acc[8][4];
        uint32_t qf[8][2];
        float m_run = -INFINITY, l_run = 0.f;
        int cur_g = -1, next_g = 0, fl = 0;
        bool sig0 = false;
        const int krow = warp * 16 + (lane & 7);
        const int kch = lane >> 3;
        const int vrow = warp * 16 + ((lane >> 4) << 3) + (lane & 7);
        const int vch = (lane >> 3) & 1;
        float* spart = (float*)(smem + SM_PART);
        float* sml = (float*)(smem + SM_ML);

        int s = 0;
        uint32_t ph = 0;
        while (true) {
            mbar_wait(bar_full + s * 8, ph);
            const int t = tile_id[s];
            const int g = (t < 0) ? NG : (t / TILES_PER_G);
            if (g != cur_g) {
                if (cur_g >= 0) {
                    if (cur_g >= HKV) mbar_wait(bar_zero, 0);
                    float* pp = spart + (fl * NCW + warp) * 2 * DH;
                    float* pm = sml + (fl * NCW + warp) * 4;
                    float l = l_run;
                    l += __shfl_xor_sync(0xffffffffu, l, 1);
                    l += __shfl_xor_sync(0xffffffffu, l, 2);
                    if (t4 == 0) {
#pragma unroll
                        for (int mt = 0; mt < 8; mt++) {
                            *(float2*)(pp + (mt * 16 + g8) * 2) = make_float2(acc[mt][0], acc[mt][1]);
                            *(float2*)(pp + (mt * 16 + g8 + 8) * 2) = make_float2(acc[mt][2], acc[mt][3]);
                        }
                        if (g8 < 2) *(float2*)(pm + g8 * 2) = make_float2(m_run, l);
                    }
                    bar_sync(BAR_CONS, NCT);
                    const float* bp = spart + fl * NCW * 2 * DH;
                    const float* bm = sml + fl * NCW * 4;
                    float4 ml[NCW];
#pragma unroll
                    for (int wv = 0; wv < NCW; wv++) ml[wv] = *(const float4*)(bm + wv * 4);
                    float M0 = ml[0].x, M1 = ml[0].z;
#pragma unroll
                    for (int wv = 1; wv < NCW; wv++) { M0 = fmaxf(M0, ml[wv].x); M1 = fmaxf(M1, ml[wv].z); }
                    float L0 = 0.f, L1 = 0.f;
#pragma unroll
                    for (int wv = 0; wv < NCW; wv++) {
                        ml[wv].x = ex2(ml[wv].x - M0);
                        ml[wv].z = ex2(ml[wv].z - M1);
                        L0 = fmaf(ml[wv].x, ml[wv].y, L0);
                        L1 = fmaf(ml[wv].z, ml[wv].w, L1);
                    }
#pragma unroll
                    for (int d = tid; d < DH; d += NCT) {
                        float o0 = 0.f, o1 = 0.f;
#pragma unroll
                        for (int wv = 0; wv < NCW; wv++) {
                            const float2 f = *(const float2*)(bp + wv * 2 * DH + d * 2);
                            o0 = fmaf(ml[wv].x, f.x, o0);
                            o1 = fmaf(ml[wv].z, f.y, o1);
                        }
                        float* rp = g_rec + ((size_t)(cur_g * 8 + (d >> 5)) * MAX_CTAS + cta) * REC_W;
                        __stcg(rp + lane, nz(o0));
                        __stcg(rp + 4 * MAX_CTAS * REC_W + lane, nz(o1));
                        if (lane < 2) {
                            const float4 f = make_float4(nz(lane ? M1 : M0), nz(lane ? L1 : L0), 1.f, 1.f);
                            __stcg((float4*)(rp + lane * 4 * MAX_CTAS * REC_W + 32), f);
                        }
                    }
                    fl ^= 1;
                    next_g = cur_g + 1;
                }
                for (; next_g < g; next_g++) {
                    mbar_wait(bar_q + next_g * 8, 0);
                    if (next_g >= HKV) {
                        if (!sig0) { if (lane == 0) mbar_arrive(bar_sig); sig0 = true; }
                        mbar_wait(bar_zero, 0);
                    }
                    for (int idx = tid; idx < 2 * DH; idx += NCT) {
                        float* rp = g_rec + ((size_t)(next_g * 8 + (idx >> 5)) * MAX_CTAS + cta) * REC_W;
                        __stcg(rp + lane, -0.0f);
                        if (lane < 4) __stcg(rp + 32 + lane, lane == 0 ? -INFINITY : (lane == 1 ? -0.0f : 1.0f));
                    }
                }
                if (!sig0 && g >= HKV) { if (lane == 0) mbar_arrive(bar_sig); sig0 = true; }
                if (t < 0) break;
                cur_g = g;
                mbar_wait(bar_q + g * 8, 0);
                const uint32_t* sq32 =
                    (const uint32_t*)(smem + SM_Q) + ((g >> 4) * QN + ((g & 15) * 2 + (g8 & 1)) * DH) / 2;
#pragma unroll
                for (int ks = 0; ks < 8; ks++) {
                    const uint32_t v0 = sq32[ks * 8 + t4], v1 = sq32[ks * 8 + 4 + t4];
                    qf[ks][0] = (g8 < 2) ? v0 : 0u;
                    qf[ks][1] = (g8 < 2) ? v1 : 0u;
                }
#pragma unroll
                for (int mt = 0; mt < 8; mt++) acc[mt][0] = acc[mt][1] = acc[mt][2] = acc[mt][3] = 0.f;
                m_run = -INFINITY;
                l_run = 0.f;
            }
            const uint32_t kb = sbase + SM_RING + s * STAGE_BYTES, vb = kb + TILE_BYTES;
            uint32_t kf[2][4][4], vf[8][4];
#pragma unroll
            for (int nt = 0; nt < 2; nt++)
#pragma unroll
                for (int j = 0; j < 4; j++) {
                    const int row = krow + nt * 8;
                    const int ch = (j & 1) * 4 + kch;
                    ldsm_x4(kf[nt][j], kb + (j >> 1) * (TILE * 128) + row * 128 + ((ch ^ (row & 7)) << 4));
                }
#pragma unroll
            for (int mt = 0; mt < 8; mt++) {
                const int ch = (mt & 3) * 2 + vch;
                ldsm_x4_t(vf[mt], vb + (mt >> 2) * (TILE * 128) + vrow * 128 + ((ch ^ (vrow & 7)) << 4));
            }
            __syncwarp();
            if (lane == 0) mbar_arrive(bar_empty + s * 8);
            if (++s == STAGES) { s = 0; ph ^= 1; }

            float sc[2][2][4];
#pragma unroll
            for (int nt = 0; nt < 2; nt++)
#pragma unroll
                for (int hh = 0; hh < 2; hh++) {
                    sc[nt][hh][0] = sc[nt][hh][1] = sc[nt][hh][2] = sc[nt][hh][3] = 0.f;
#pragma unroll
                    for (int jj = 0; jj < 2; jj++) {
                        const int j = hh * 2 + jj;
                        mma_bf16(sc[nt][hh], qf[2 * j][0], 0u, qf[2 * j][1], 0u, kf[nt][j][0], kf[nt][j][1]);
                        mma_bf16(sc[nt][hh], qf[2 * j + 1][0], 0u, qf[2 * j + 1][1], 0u, kf[nt][j][2], kf[nt][j][3]);
                    }
                }
            const float s0 = (sc[0][0][0] + sc[0][1][0]) * SCALE, s1 = (sc[0][0][1] + sc[0][1][1]) * SCALE;
            const float s2 = (sc[1][0][0] + sc[1][1][0]) * SCALE, s3 = (sc[1][0][1] + sc[1][1][1]) * SCALE;
            float mx = fmaxf(fmaxf(s0, s1), fmaxf(s2, s3));
            mx = fmaxf(mx, __shfl_xor_sync(0xffffffffu, mx, 1));
            mx = fmaxf(mx, __shfl_xor_sync(0xffffffffu, mx, 2));
            const float m_new = fmaxf(m_run, mx);
            const float alpha = ex2(m_run - m_new);
            m_run = m_new;
            const float p0 = ex2(s0 - m_new), p1 = ex2(s1 - m_new), p2 = ex2(s2 - m_new), p3 = ex2(s3 - m_new);
            l_run = fmaf(l_run, alpha, (p0 + p1) + (p2 + p3));
            const uint32_t pb0 = pack_bf16(p0, p1), pb1 = pack_bf16(p2, p3);
            const float al0 = __shfl_sync(0xffffffffu, alpha, 0), al1 = __shfl_sync(0xffffffffu, alpha, 4);
            if (al0 != 1.f || al1 != 1.f) {
#pragma unroll
                for (int mt = 0; mt < 8; mt++) {
                    acc[mt][0] *= al0;
                    acc[mt][1] *= al1;
                    acc[mt][2] *= al0;
                    acc[mt][3] *= al1;
                }
            }
#pragma unroll
            for (int mt = 0; mt < 8; mt++) mma_bf16(acc[mt], vf[mt][0], vf[mt][1], vf[mt][2], vf[mt][3], pb0, pb1);
        }
        if (lane == 0) mbar_arrive(bar_sig + 8);
    } else {
        float* hb = (float*)(smem + SM_HB);
        float* hm = (float*)(smem + SM_HM);
        float* hr = (float*)(smem + SM_HR);
        {
            int slice = cta;
            *(float2*)(hb + 2 * ht) = make_float2(bf_lo(xv0), bf_hi(xv0));
            *(float2*)(hb + DM + 2 * ht) = make_float2(bf_lo(xv1), bf_hi(xv1));
            bar_sync(BAR_HELP, NHT);
            for (; slice < NSLICE;) {
                float a0[8], a1[8];
#pragma unroll
                for (int j = 0; j < 8; j++) a0[j] = a1[j] = 0.f;
#pragma unroll
                for (int i = 0; i < 8; i++) {
                    const float x0 = hb[r0 + 72 * i], x1 = hb[DM + r0 + 72 * i];
                    const uint32_t u[4] = {w[i].x, w[i].y, w[i].z, w[i].w};
#pragma unroll
                    for (int j = 0; j < 4; j++) {
                        const float lo = bf_lo(u[j]), hi = bf_hi(u[j]);
                        a0[2 * j] = fmaf(x0, lo, a0[2 * j]);
                        a0[2 * j + 1] = fmaf(x0, hi, a0[2 * j + 1]);
                        a1[2 * j] = fmaf(x1, lo, a1[2 * j]);
                        a1[2 * j + 1] = fmaf(x1, hi, a1[2 * j + 1]);
                    }
                }
#pragma unroll
                for (int j = 0; j < 8; j++) {
#pragma unroll
                    for (int o = 4; o < 32; o <<= 1) {
                        a0[j] += __shfl_xor_sync(0xffffffffu, a0[j], o);
                        a1[j] += __shfl_xor_sync(0xffffffffu, a1[j], o);
                    }
                }
                if (lane < 4) {
#pragma unroll
                    for (int j = 0; j < 8; j++) {
                        hr[hw * 64 + lane * 8 + j] = a0[j];
                        hr[hw * 64 + 32 + lane * 8 + j] = a1[j];
                    }
                }
                bar_sync(BAR_HELP, NHT);
                if (ht < 32) {
                    float s0 = 0.f, s1 = 0.f;
#pragma unroll
                    for (int wv = 0; wv < NHW; wv++) {
                        const float2 f = *(const float2*)(hr + wv * 64 + ht * 2);
                        s0 += f.x;
                        s1 += f.y;
                    }
                    uint32_t u = pack_bf16(s0, s1);
                    if (u == 0u) u = 0x80000000u;
                    __stcg(g_q + ((ht >> 4) * QN + slice * 32) / 2 + (ht & 15), u);
                }
                slice += nc;
                if (slice < NSLICE) {
                    bar_sync(BAR_HELP, NHT);
                    const uint4* wp = (const uint4*)(wq + (size_t)r0 * QN + slice * 32 + (lane & 3) * 8);
#pragma unroll
                    for (int i = 0; i < 8; i++) w[i] = __ldg(wp + (size_t)i * 72 * QN / 8);
                }
            }
        }
        for (int g = hw; g < NG; g += NHW) {
            const uint4* src = (const uint4*)g_q + g * 32 + lane;
            uint4 v = ld_relaxed_v4(src);
            v = poll_v4(src, v);
            ((uint4*)(smem + SM_Q))[g * 32 + lane] = v;
            __syncwarp();
            if (lane == 0) mbar_arrive(bar_q + g * 8);
        }
        const int rr = ht / 9, part = ht - rr * 9;
        constexpr int MAXS = (NSLICE + 63) / 64;
        float o_b0[MAXS];
#pragma unroll 1
        for (int b = 0; b < BATCH; b++) {
            const bool live = (b == BATCH - 1);
            if (lane == 0) mbar_wait(bar_sig + b * 8, 0);
            __syncwarp();
            if (!live) {
                for (int u = cta; u < NUNIT; u += nc) {
                    const int ub = u / (NUNIT / 2), uc = u - ub * (NUNIT / 2);
                    float* dst = g_pout + (size_t)(ub * NSLICE + (ht >> 1)) * DM + uc * 16 + (ht & 1) * 8;
                    if (ht < 2 * NSLICE) {
                        __stcg((uint4*)dst, make_uint4(0u, 0u, 0u, 0u));
                        __stcg((uint4*)(dst + 4), make_uint4(0u, 0u, 0u, 0u));
                    }
                }
                __threadfence();
                __syncwarp();
                if (lane == 0) mbar_arrive(bar_zero);
            }
            int si = 0;
#pragma unroll 1
            for (int slice = cta; slice < NSLICE; slice += nc, si++) {
                float* src = g_rec + (size_t)(b * HKV * 8 + slice) * MAX_CTAS * REC_W + ht * 4;
                constexpr int NR = MAX_CTAS / 32;
                uint4 v[NR];
#pragma unroll
                for (int k = 0; k < NR; k++) v[k] = (rr + 32 * k < nc) ? make_uint4(0u, 0u, 0u, 0u) : make_uint4(1u, 1u, 1u, 1u);
                for (uint32_t it = 0;; it++) {
#pragma unroll
                    for (int k = 0; k < NR; k++)
                        if (!all_nz(v[k])) v[k] = ld_relaxed_v4(src + k * NHT * 4);
                    bool ok = true;
#pragma unroll
                    for (int k = 0; k < NR; k++) ok = ok && all_nz(v[k]);
                    if (ok) break;
                    if (it > (1u << 22)) __trap();
                }
                if (part == 8) {
#pragma unroll
                    for (int k = 0; k < NR; k++)
                        if (rr + 32 * k < nc) {
                            hm[rr + 32 * k] = __uint_as_float(v[k].x);
                            hm[MAX_CTAS + rr + 32 * k] = __uint_as_float(v[k].y);
                        }
                }
                bar_sync(BAR_HELP, NHT);
                float M = -INFINITY;
#pragma unroll
                for (int k = 0; k < NR; k++)
                    if (lane + 32 * k < nc) M = fmaxf(M, hm[lane + 32 * k]);
#pragma unroll
                for (int o = 16; o > 0; o >>= 1) M = fmaxf(M, __shfl_xor_sync(0xffffffffu, M, o));
                float4 a = make_float4(0.f, 0.f, 0.f, 0.f);
#pragma unroll
                for (int k = 0; k < NR; k++)
                    if (rr + 32 * k < nc) {
                        const float e = ex2(hm[rr + 32 * k] - M);
                        a.x = fmaf(e, __uint_as_float(v[k].x), a.x);
                        a.y = fmaf(e, __uint_as_float(v[k].y), a.y);
                        a.z = fmaf(e, __uint_as_float(v[k].z), a.z);
                        a.w = fmaf(e, __uint_as_float(v[k].w), a.w);
                    }
                *(float4*)(hb + ht * 4) = a;
                bar_sync(BAR_HELP, NHT);
                float o0 = 0.f, o1 = 0.f, L = hb[lane * REC_W + 33];
#pragma unroll
                for (int r = 0; r < 32; r += 2) {
                    o0 += hb[r * REC_W + lane];
                    o1 += hb[(r + 1) * REC_W + lane];
                }
#pragma unroll
                for (int o = 16; o > 0; o >>= 1) L += __shfl_xor_sync(0xffffffffu, L, o);
                const float ob = __bfloat162float(__float2bfloat16((o0 + o1) / L));
                float oa = ob;
#pragma unroll
                for (int i = 0; i < MAXS; i++)
                    if (i == si) {
                        if (!live) o_b0[i] = ob;
                        oa = o_b0[i];
                    }
                __nv_bfloat16* ho = (__nv_bfloat16*)(smem + SM_HO) + hw * 64;
                ho[lane] = __float2bfloat16(oa);
                ho[32 + lane] = __float2bfloat16(ob);
                if (live && si > 0) {
                    bar_sync(BAR_HELP, NHT);
                    const uint32_t* gw = (const uint32_t*)(wo + (size_t)slice * 32 * DM) + ht;
                    for (int r = 0; r < 32; r++) *(uint32_t*)(smem + SM_WO + r * WO_PITCH + ht * 4) = __ldg(gw + r * (DM / 2));
                    bar_sync(BAR_HELP, NHT);
                } else if (live) {
                    mbar_wait(bar_sig + 16, 0);
                }
                __syncwarp();
                {
                    const int g8 = lane >> 2, t4 = lane & 3;
                    const uint32_t* ho32 = (const uint32_t*)ho + (g8 & 1) * 16 + t4;
                    uint32_t bf[4];
#pragma unroll
                    for (int i = 0; i < 4; i++) bf[i] = (g8 < 2) ? ho32[i * 4] : 0u;
                    const uint32_t wa = sbase + SM_WO + (((lane >> 4) << 3) + (lane & 7)) * WO_PITCH +
                                        (hw * 64 + ((lane >> 3) & 1) * 8) * 2;
                    uint32_t af[4][2][4];
#pragma unroll
                    for (int mt = 0; mt < 4; mt++) {
                        ldsm_x4_t(af[mt][0], wa + mt * 32);
                        ldsm_x4_t(af[mt][1], wa + mt * 32 + 16 * WO_PITCH);
                    }
                    float c[4][4];
#pragma unroll
                    for (int mt = 0; mt < 4; mt++) {
                        c[mt][0] = c[mt][1] = c[mt][2] = c[mt][3] = 0.f;
                        mma_bf16(c[mt], af[mt][0][0], af[mt][0][1], af[mt][0][2], af[mt][0][3], bf[0], bf[1]);
                    }
#pragma unroll
                    for (int mt = 0; mt < 4; mt++)
                        mma_bf16(c[mt], af[mt][1][0], af[mt][1][1], af[mt][1][2], af[mt][1][3], bf[2], bf[3]);
                    float* hy = (float*)(smem + SM_HY) + hw * 128;
                    if (t4 == 0) {
#pragma unroll
                        for (int mt = 0; mt < 4; mt++) {
                            hy[mt * 16 + g8] = c[mt][0];
                            hy[mt * 16 + g8 + 8] = c[mt][2];
                            hy[64 + mt * 16 + g8] = c[mt][1];
                            hy[64 + mt * 16 + g8 + 8] = c[mt][3];
                        }
                    }
                    __syncwarp();
                    const float4 y = *(const float4*)(hy + lane * 4);
                    if (live)
                        __stcg((float4*)(g_pout + (size_t)((lane >> 4) * NSLICE + slice) * DM + hw * 64 + (lane & 15) * 4),
                               make_float4(nz(y.x), nz(y.y), nz(y.z), nz(y.w)));
                }
#pragma unroll
                for (int k = 0; k < NR; k++)
                    if (rr + 32 * k < nc) __stcg((uint4*)(src + k * NHT * 4), make_uint4(0u, 0u, 0u, 0u));
                if (live) {
                    if (ht < 32) __stcg(g_q + ((ht >> 4) * QN + slice * 32) / 2 + (ht & 15), 0u);
                    if (slice == NSLICE - 1 && ht == 0) g_tile_counter = 0u;
                }
                bar_sync(BAR_HELP, NHT);
            }
#pragma unroll 1
            for (int u = cta; u < NUNIT; u += nc) {
                const int ub = u / (NUNIT / 2), uc = u - ub * (NUNIT / 2);
                float* src = g_pout + (size_t)(ub * NSLICE + (ht >> 1)) * DM + uc * 16 + (ht & 1) * 8;
                if (ht < 2 * NSLICE) {
                    uint4 v0 = make_uint4(0u, 0u, 0u, 0u), v1 = v0;
                    for (uint32_t it = 0; live; it++) {
                        if (!all_nz(v0)) v0 = ld_relaxed_v4(src);
                        if (!all_nz(v1)) v1 = ld_relaxed_v4(src + 4);
                        if (all_nz(v0) && all_nz(v1)) break;
                        if (it > (1u << 22)) __trap();
                    }
                    *(uint4*)(hb + (ht >> 1) * 20 + (ht & 1) * 8) = v0;
                    *(uint4*)(hb + (ht >> 1) * 20 + (ht & 1) * 8 + 4) = v1;
                }
                bar_sync(BAR_HELP, NHT);
                if (hw < 8) {
                    const float* hp = hb + (lane >> 1) * 20 + hw * 2 + (lane & 1);
                    float a = 0.f;
#pragma unroll
                    for (int i = 0; i < 8; i++) a += hp[i * 16 * 20];
#pragma unroll
                    for (int o = 16; o > 1; o >>= 1) a += __shfl_xor_sync(0xffffffffu, a, o);
                    const float a1 = __shfl_down_sync(0xffffffffu, a, 1);
                    if (live && lane == 0) ((uint32_t*)out)[u * 8 + hw] = pack_bf16(a, a1);
                }
                bar_sync(BAR_HELP, NHT);
            }
        }
    }
}

typedef CUresult (*EncodeTiledFn)(CUtensorMap*, CUtensorMapDataType, cuuint32_t, void*, const cuuint64_t*,
                                  const cuuint64_t*, const cuuint32_t*, const cuuint32_t*, CUtensorMapInterleave,
                                  CUtensorMapSwizzle, CUtensorMapL2promotion, CUtensorMapFloatOOBfill);

}

extern "C" void kernel_launch(void* const* d_in, const int* in_sizes, int n_in, void* d_out, int out_size) {
    (void)in_sizes; (void)n_in; (void)out_size;
    const __nv_bfloat16* x = (const __nv_bfloat16*)d_in[0];
    void* kc = d_in[1];
    void* vc = d_in[2];
    const __nv_bfloat16* wq = (const __nv_bfloat16*)d_in[3];
    const __nv_bfloat16* wo = (const __nv_bfloat16*)d_in[4];

    static EncodeTiledFn enc = nullptr;
    static int num_sms = 0;
    if (!enc) {
        cudaDriverEntryPointQueryResult qr;
        cudaGetDriverEntryPoint("cuTensorMapEncodeTiled", (void**)&enc, cudaEnableDefault, &qr);
        int dev = 0;
        cudaGetDevice(&dev);
        cudaDeviceGetAttribute(&num_sms, cudaDevAttrMultiProcessorCount, dev);
        cudaFuncSetAttribute(gqa_decode_kernel, cudaFuncAttributeMaxDynamicSharedMemorySize, SMEM_BYTES);
    }
    CUtensorMap mk, mv;
    cuuint64_t gd[3] = {64, (cuuint64_t)NG * SK, 2};
    cuuint64_t gs[2] = {256, 128};
    cuuint32_t box[3] = {64, TILE, 2};
    cuuint32_t es[3] = {1, 1, 1};
    enc(&mk, CU_TENSOR_MAP_DATA_TYPE_BFLOAT16, 3, kc, gd, gs, box, es, CU_TENSOR_MAP_INTERLEAVE_NONE,
        CU_TENSOR_MAP_SWIZZLE_128B, CU_TENSOR_MAP_L2_PROMOTION_L2_256B, CU_TENSOR_MAP_FLOAT_OOB_FILL_NONE);
    enc(&mv, CU_TENSOR_MAP_DATA_TYPE_BFLOAT16, 3, vc, gd, gs, box, es, CU_TENSOR_MAP_INTERLEAVE_NONE,
        CU_TENSOR_MAP_SWIZZLE_128B, CU_TENSOR_MAP_L2_PROMOTION_L2_256B, CU_TENSOR_MAP_FLOAT_OOB_FILL_NONE);
    int grid = num_sms < MAX_CTAS ? num_sms : MAX_CTAS;
    gqa_decode_kernel<<<grid, NTHREADS, SMEM_BYTES>>>(mk, mv, x, wq, wo, (__nv_bfloat16*)d_out);
}
```
